```python
import torch

def _softmax(x, axis=-1):
    return torch.softmax(x, dim=axis)
def _gelu(x):
    return torch.nn.functional.gelu(x, approximate="tanh")
def _silu(x):
    return torch.nn.functional.silu(x)
def _sigmoid(x):
    return torch.sigmoid(x)
def _layernorm(x, axis=-1, eps=1e-5):
    m = x.mean(dim=axis, keepdim=True)
    v = x.var(dim=axis, keepdim=True, unbiased=False)
    return (x - m) / torch.sqrt(v + eps)
def _scatter_add(tgt, idx, src, axis=0):
    return tgt.clone().index_add_(axis, idx, src)
def _segment_sum(src, seg, n):
    out = torch.zeros((n,) + src.shape[1:], dtype=src.dtype)
    return out.index_add_(0, seg, src)
def _pad(x, pw):
    flat = tuple(v for pair in reversed(pw) for v in pair)
    return torch.nn.functional.pad(x, flat)

kernel_name = 'standalone__modern_conv_block_replknet__vision'

def setup_inputs():

    _w = (lambda a: (lambda t: t.to(torch.bfloat16) if t.is_floating_point() else t)(torch.as_tensor(a)))
    H = W = 512
    C = 96
    K = 3
    return {
        "x": _w((lambda *s: torch.randn(*s, dtype=torch.bfloat16) * 0.05)(1, H, W, C)),
        "dw_large": _w((lambda *s: torch.randn(*s, dtype=torch.bfloat16) * 0.4)(K, K, C) * (1.0 / K)),
        "dw_small": _w((lambda *s: torch.randn(*s, dtype=torch.bfloat16) * 0.4)(5, 5, C) * 0.2),
        "w1": _w((lambda *s: torch.randn(*s, dtype=torch.bfloat16) * 0.4)(C, 4 * C) * (C ** -0.5)),
        "w2": _w((lambda *s: torch.randn(*s, dtype=torch.bfloat16) * 0.1)(4 * C, C) * ((4 * C) ** -0.5)),
    }

def reference(x, dw_large, dw_small, w1, w2):
    B, H, W, C = x.shape
    Kl = dw_large.shape[0]
    pl = (Kl - 1) // 2
    xpl = _pad(x, ((0,0),(pl,pl),(pl,pl),(0,0)))
    out = torch.zeros_like(x)
    for i in range(Kl):
        for j in range(Kl):
            out = out + xpl[:, i:i+H, j:j+W, :] * dw_large[i, j][None, None, None, :]
    Ks = dw_small.shape[0]
    ps = (Ks - 1) // 2
    xps = _pad(x, ((0,0),(ps,ps),(ps,ps),(0,0)))
    for i in range(Ks):
        for j in range(Ks):
            out = out + xps[:, i:i+H, j:j+W, :] * dw_small[i, j][None, None, None, :]
    h = _layernorm(out, axis=-1)
    h = _gelu(torch.einsum('bhwc,ce->bhwe', h, w1))
    h = torch.einsum('bhwe,ec->bhwc', h, w2)
    return x + h
```

```cpp
#include <cuda_runtime.h>
#include <cuda_bf16.h>
#include <cuda_fp16.h>
#include <cuda.h>
#include <stdint.h>

namespace {

constexpr int IMG_H = 512, IMG_W = 512, CH = 96, HID = 384;
constexpr int SW = 32;
constexpr int RB = 64;
constexpr int NT = RB / 2;
constexpr int NSTG = NT + 2;
#define NS 4
#define NB 2
#define NCH 4
#define KSP 2
#define P1MID 1
#define P1LAST 1
#define ACC2_F16 1
#define REG_CONS 184
#define REG_CONV 136
constexpr int CN = HID / NCH;
constexpr int CR = CN / 4;
constexpr int NP = CN / 16 / KSP;

constexpr int XROW = (SW + 4) * CH * 2;
constexpr int XSTG = 2 * XROW;
constexpr int CPITCH = 208;
constexpr int CGRP = 16 * CPITCH + 64;
constexpr int CBUF = 4 * CGRP;
constexpr int OFF_W1 = 0;
constexpr int OFF_W2 = CH * HID * 2;
constexpr int OFF_X = 2 * CH * HID * 2;
constexpr int OFF_C = OFF_X + NS * XSTG;
constexpr int OFF_BAR = OFF_C + NB * CBUF;
constexpr int OFF_RED = OFF_BAR + 16 * NS;
constexpr int SMEM_BYTES = OFF_RED + 64;
static_assert(SMEM_BYTES <= 232448, "smem");

constexpr int BAR_FULL = 1, BAR_EMPTY = 1 + NB, BAR_CONS = 1 + 2 * NB;

constexpr float GA = 0.3292034911525734f;
constexpr uint32_t GK2 = 0x40d940d9u;
constexpr float INV2A = 1.5188174288475842f;

template <int SCALE_D>
__device__ __forceinline__ void wg_n96_h(uint32_t* d, const uint32_t* a, uint64_t desc) {
    asm volatile("wgmma.mma_async.sync.aligned.m64n96k16.f16.f16.f16 {"
        "%0,%1,%2,%3,%4,%5,%6,%7,%8,%9,%10,%11,%12,%13,%14,%15,"
        "%16,%17,%18,%19,%20,%21,%22,%23},"
        "{%24,%25,%26,%27}, %28, %29, 1, 1, 1;"
        : "+r"(d[0]), "+r"(d[1]), "+r"(d[2]), "+r"(d[3]), "+r"(d[4]), "+r"(d[5]), "+r"(d[6]), "+r"(d[7]),
          "+r"(d[8]), "+r"(d[9]), "+r"(d[10]), "+r"(d[11]), "+r"(d[12]), "+r"(d[13]), "+r"(d[14]), "+r"(d[15]),
          "+r"(d[16]), "+r"(d[17]), "+r"(d[18]), "+r"(d[19]), "+r"(d[20]), "+r"(d[21]), "+r"(d[22]), "+r"(d[23])
        : "r"(a[0]), "r"(a[1]), "r"(a[2]), "r"(a[3]), "l"(desc), "n"(SCALE_D));
}

template <int SCALE_D>
__device__ __forceinline__ void wg_n128_h(uint32_t* d, const uint32_t* a, uint64_t desc) {
    asm volatile("wgmma.mma_async.sync.aligned.m64n128k16.f16.f16.f16 {"
        "%0,%1,%2,%3,%4,%5,%6,%7,%8,%9,%10,%11,%12,%13,%14,%15,"
        "%16,%17,%18,%19,%20,%21,%22,%23,%24,%25,%26,%27,%28,%29,%30,%31},"
        "{%32,%33,%34,%35}, %36, %37, 1, 1, 1;"
        : "+r"(d[0]), "+r"(d[1]), "+r"(d[2]), "+r"(d[3]), "+r"(d[4]), "+r"(d[5]), "+r"(d[6]), "+r"(d[7]),
          "+r"(d[8]), "+r"(d[9]), "+r"(d[10]), "+r"(d[11]), "+r"(d[12]), "+r"(d[13]), "+r"(d[14]), "+r"(d[15]),
          "+r"(d[16]), "+r"(d[17]), "+r"(d[18]), "+r"(d[19]), "+r"(d[20]), "+r"(d[21]), "+r"(d[22]), "+r"(d[23]),
          "+r"(d[24]), "+r"(d[25]), "+r"(d[26]), "+r"(d[27]), "+r"(d[28]), "+r"(d[29]), "+r"(d[30]), "+r"(d[31])
        : "r"(a[0]), "r"(a[1]), "r"(a[2]), "r"(a[3]), "l"(desc), "n"(SCALE_D));
}

template <int SCALE_D>
__device__ __forceinline__ void wg_n192_h(uint32_t* d, const uint32_t* a, uint64_t desc) {
    asm volatile("wgmma.mma_async.sync.aligned.m64n192k16.f16.f16.f16 {"
        "%0,%1,%2,%3,%4,%5,%6,%7,%8,%9,%10,%11,%12,%13,%14,%15,"
        "%16,%17,%18,%19,%20,%21,%22,%23,%24,%25,%26,%27,%28,%29,%30,%31,"
        "%32,%33,%34,%35,%36,%37,%38,%39,%40,%41,%42,%43,%44,%45,%46,%47},"
        "{%48,%49,%50,%51}, %52, %53, 1, 1, 1;"
        : "+r"(d[0]), "+r"(d[1]), "+r"(d[2]), "+r"(d[3]), "+r"(d[4]), "+r"(d[5]), "+r"(d[6]), "+r"(d[7]),
          "+r"(d[8]), "+r"(d[9]), "+r"(d[10]), "+r"(d[11]), "+r"(d[12]), "+r"(d[13]), "+r"(d[14]), "+r"(d[15]),
          "+r"(d[16]), "+r"(d[17]), "+r"(d[18]), "+r"(d[19]), "+r"(d[20]), "+r"(d[21]), "+r"(d[22]), "+r"(d[23]),
          "+r"(d[24]), "+r"(d[25]), "+r"(d[26]), "+r"(d[27]), "+r"(d[28]), "+r"(d[29]), "+r"(d[30]), "+r"(d[31]),
          "+r"(d[32]), "+r"(d[33]), "+r"(d[34]), "+r"(d[35]), "+r"(d[36]), "+r"(d[37]), "+r"(d[38]), "+r"(d[39]),
          "+r"(d[40]), "+r"(d[41]), "+r"(d[42]), "+r"(d[43]), "+r"(d[44]), "+r"(d[45]), "+r"(d[46]), "+r"(d[47])
        : "r"(a[0]), "r"(a[1]), "r"(a[2]), "r"(a[3]), "l"(desc), "n"(SCALE_D));
}

template <int SCALE_D>
__device__ __forceinline__ void wg_n96_f(float* d, const uint32_t* a, uint64_t desc) {
    asm volatile("wgmma.mma_async.sync.aligned.m64n96k16.f32.f16.f16 {"
        "%0,%1,%2,%3,%4,%5,%6,%7,%8,%9,%10,%11,%12,%13,%14,%15,"
        "%16,%17,%18,%19,%20,%21,%22,%23,%24,%25,%26,%27,%28,%29,%30,%31,"
        "%32,%33,%34,%35,%36,%37,%38,%39,%40,%41,%42,%43,%44,%45,%46,%47},"
        "{%48,%49,%50,%51}, %52, %53, 1, 1, 1;"
        : "+f"(d[0]), "+f"(d[1]), "+f"(d[2]), "+f"(d[3]), "+f"(d[4]), "+f"(d[5]), "+f"(d[6]), "+f"(d[7]),
          "+f"(d[8]), "+f"(d[9]), "+f"(d[10]), "+f"(d[11]), "+f"(d[12]), "+f"(d[13]), "+f"(d[14]), "+f"(d[15]),
          "+f"(d[16]), "+f"(d[17]), "+f"(d[18]), "+f"(d[19]), "+f"(d[20]), "+f"(d[21]), "+f"(d[22]), "+f"(d[23]),
          "+f"(d[24]), "+f"(d[25]), "+f"(d[26]), "+f"(d[27]), "+f"(d[28]), "+f"(d[29]), "+f"(d[30]), "+f"(d[31]),
          "+f"(d[32]), "+f"(d[33]), "+f"(d[34]), "+f"(d[35]), "+f"(d[36]), "+f"(d[37]), "+f"(d[38]), "+f"(d[39]),
          "+f"(d[40]), "+f"(d[41]), "+f"(d[42]), "+f"(d[43]), "+f"(d[44]), "+f"(d[45]), "+f"(d[46]), "+f"(d[47])
        : "r"(a[0]), "r"(a[1]), "r"(a[2]), "r"(a[3]), "l"(desc), "n"(SCALE_D));
}

__device__ __forceinline__ void wg_fence() { asm volatile("wgmma.fence.sync.aligned;" ::: "memory"); }
__device__ __forceinline__ void wg_commit() { asm volatile("wgmma.commit_group.sync.aligned;" ::: "memory"); }
template <int N> __device__ __forceinline__ void wg_wait() { asm volatile("wgmma.wait_group.sync.aligned %0;" ::"n"(N) : "memory"); }
template <int N> __device__ __forceinline__ void pin(uint32_t* r) {
#pragma unroll
    for (int i = 0; i < N; i++) asm volatile("" : "+r"(r[i])::"memory");
}
template <int N> __device__ __forceinline__ void pin(float* r) {
#pragma unroll
    for (int i = 0; i < N; i++) asm volatile("" : "+f"(r[i])::"memory");
}
__device__ __forceinline__ uint64_t mk_desc(uint32_t lo, uint32_t hi) { return ((uint64_t)hi << 32) | lo; }

__device__ __forceinline__ void bar_sync(int id, int n) { asm volatile("bar.sync %0, %1;" ::"r"(id), "r"(n) : "memory"); }
__device__ __forceinline__ void bar_arrive(int id, int n) { asm volatile("bar.arrive %0, %1;" ::"r"(id), "r"(n) : "memory"); }
__device__ __forceinline__ void mbar_init(uint32_t a, uint32_t cnt) { asm volatile("mbarrier.init.shared::cta.b64 [%0], %1;" ::"r"(a), "r"(cnt) : "memory"); }
__device__ __forceinline__ void mbar_arrive(uint32_t a) { asm volatile("mbarrier.arrive.shared::cta.b64 _, [%0];" ::"r"(a) : "memory"); }
__device__ __forceinline__ void mbar_expect_tx(uint32_t a, uint32_t bytes) { asm volatile("mbarrier.arrive.expect_tx.shared::cta.b64 _, [%0], %1;" ::"r"(a), "r"(bytes) : "memory"); }
__device__ __forceinline__ void mbar_wait(uint32_t a, uint32_t parity) {
    uint32_t ok;
    int guard = 0;
    do {
        asm volatile("{.reg .pred p; mbarrier.try_wait.parity.shared::cta.b64 p, [%1], %2; selp.u32 %0, 1, 0, p;}" : "=r"(ok) : "r"(a), "r"(parity) : "memory");
        if (++guard > (1 << 22)) __trap();
    } while (!ok);
}
__device__ __forceinline__ void tma_load3(uint32_t dst, const CUtensorMap* tm, uint32_t bar, int c0, int c1, int c2) {
    asm volatile("cp.async.bulk.tensor.3d.shared::cluster.global.mbarrier::complete_tx::bytes [%0], [%1, {%3, %4, %5}], [%2];"
                 ::"r"(dst), "l"(tm), "r"(bar), "r"(c0), "r"(c1), "r"(c2) : "memory");
}
__device__ __forceinline__ uint32_t lds32(uint32_t a) { uint32_t v; asm volatile("ld.shared.b32 %0, [%1];" : "=r"(v) : "r"(a)); return v; }
__device__ __forceinline__ void sts32(uint32_t a, uint32_t v) { asm volatile("st.shared.b32 [%0], %1;" ::"r"(a), "r"(v)); }
__device__ __forceinline__ void sts128(uint32_t a, uint32_t x, uint32_t y, uint32_t z, uint32_t w) { asm volatile("st.shared.v4.b32 [%0], {%1,%2,%3,%4};" ::"r"(a), "r"(x), "r"(y), "r"(z), "r"(w)); }
__device__ __forceinline__ void ldsm4(uint32_t* r, uint32_t a) {
    asm volatile("ldmatrix.sync.aligned.m8n8.x4.shared.b16 {%0,%1,%2,%3}, [%4];" : "=r"(r[0]), "=r"(r[1]), "=r"(r[2]), "=r"(r[3]) : "r"(a));
}
__device__ __forceinline__ void ldg128(uint32_t* r, const void* p) {
    asm volatile("ld.global.nc.L1::no_allocate.v4.b32 {%0,%1,%2,%3}, [%4];" : "=r"(r[0]), "=r"(r[1]), "=r"(r[2]), "=r"(r[3]) : "l"(p));
}
__device__ __forceinline__ void stg128(void* p, uint32_t x, uint32_t y, uint32_t z, uint32_t w) {
    asm volatile("st.global.L1::no_allocate.v4.b32 [%0], {%1,%2,%3,%4};" ::"l"(p), "r"(x), "r"(y), "r"(z), "r"(w));
}
__device__ __forceinline__ uint32_t bfma(uint32_t a, uint32_t b, uint32_t c) { uint32_t d; asm("fma.rn.bf16x2 %0, %1, %2, %3;" : "=r"(d) : "r"(a), "r"(b), "r"(c)); return d; }
__device__ __forceinline__ uint32_t bmul(uint32_t a, uint32_t b) { uint32_t d; asm("mul.rn.bf16x2 %0, %1, %2;" : "=r"(d) : "r"(a), "r"(b)); return d; }
__device__ __forceinline__ uint32_t badd(uint32_t a, uint32_t b) { uint32_t d; asm("add.rn.bf16x2 %0, %1, %2;" : "=r"(d) : "r"(a), "r"(b)); return d; }
__device__ __forceinline__ float bf_lo(uint32_t v) { uint32_t d; asm("prmt.b32 %0, %1, 0, 0x1044;" : "=r"(d) : "r"(v)); return __uint_as_float(d); }
__device__ __forceinline__ float bf_hi(uint32_t v) { return __uint_as_float(v & 0xffff0000u); }
__device__ __forceinline__ uint32_t pack_h2(float lo, float hi) { uint32_t d; asm("cvt.rn.f16x2.f32 %0, %1, %2;" : "=r"(d) : "f"(hi), "f"(lo)); return d; }
__device__ __forceinline__ uint32_t pack_b2(float lo, float hi) { uint32_t d; asm("cvt.rn.bf16x2.f32 %0, %1, %2;" : "=r"(d) : "f"(hi), "f"(lo)); return d; }
__device__ __forceinline__ uint32_t gelu2(uint32_t s) {
    uint32_t p, u, t, y;
    asm("fma.rn.f16x2 %0, %1, %1, %2;" : "=r"(p) : "r"(s), "r"(GK2));
    asm("mul.rn.f16x2 %0, %1, %2;" : "=r"(u) : "r"(s), "r"(p));
    asm("tanh.approx.f16x2 %0, %1;" : "=r"(t) : "r"(u));
    asm("fma.rn.f16x2 %0, %1, %2, %1;" : "=r"(y) : "r"(s), "r"(t));
    return y;
}

template <int S>
__device__ __forceinline__ void conv_row(const uint32_t (&x)[S + 4], const uint32_t (&w)[25], uint32_t (&acc)[4][S], uint32_t out_addr) {
#pragma unroll
    for (int i = 4; i >= 0; i--) {
        uint32_t t[S];
#pragma unroll
        for (int p = 0; p < S; p++) t[p] = (i == 0) ? bmul(x[p], w[0]) : bfma(x[p], w[i * 5], acc[4 - i][p]);
#pragma unroll
        for (int j = 1; j < 5; j++)
#pragma unroll
            for (int p = 0; p < S; p++) t[p] = bfma(x[p + j], w[i * 5 + j], t[p]);
#pragma unroll
        for (int p = 0; p < S; p++) {
            if (i == 4) sts32(out_addr + p * CPITCH, t[p]);
            else acc[3 - i][p] = t[p];
        }
    }
}

template <int J, int SC> __device__ __forceinline__ void gemm1_step(uint32_t* h, const uint32_t* a, uint32_t dlo, int kk) {
    const uint64_t d = mk_desc(dlo + ((2 * kk * 48 + J * (CN / 8)) * 128 >> 4), 128 >> 4);
    if (CN == 96) wg_n96_h<SC>(h, a, d);
    else if (CN == 128) wg_n128_h<SC>(h, a, d);
    else wg_n192_h<SC>(h, a, d);
}
template <int J> __device__ __forceinline__ void gemm1(uint32_t* h, uint32_t* a1, uint32_t dlo) {
    pin<24>(a1);
    wg_fence();
    gemm1_step<J, 0>(h, a1, dlo, 0);
#pragma unroll
    for (int kk = 1; kk < 6; kk++) gemm1_step<J, 1>(h, a1 + 4 * kk, dlo, kk);
    wg_commit();
}

typedef uint32_t acc2_t;
constexpr int NACC2 = 24;

template <int SC> __device__ __forceinline__ void gemm2_step(acc2_t* acc, const uint32_t* a, uint32_t dlo, int ks) {
    const uint64_t d = mk_desc(dlo + (2 * ks * 12 * 128 >> 4), 128 >> 4);
    wg_n96_h<SC>(acc, a, d);
}

__device__ __forceinline__ void layernorm(uint32_t* a) {
#pragma unroll
    for (int r = 0; r < 2; r++) {
        float v[24];
        float s0 = 0.f, s1 = 0.f, q0 = 0.f, q1 = 0.f;
#pragma unroll
        for (int i = 0; i < 12; i++) {
            v[2 * i] = bf_lo(a[2 * i + r]);
            v[2 * i + 1] = bf_hi(a[2 * i + r]);
            s0 += v[2 * i]; s1 += v[2 * i + 1];
            q0 = fmaf(v[2 * i], v[2 * i], q0); q1 = fmaf(v[2 * i + 1], v[2 * i + 1], q1);
        }
        float s = s0 + s1, q = q0 + q1;
        s += __shfl_xor_sync(0xffffffffu, s, 1); q += __shfl_xor_sync(0xffffffffu, q, 1);
        s += __shfl_xor_sync(0xffffffffu, s, 2); q += __shfl_xor_sync(0xffffffffu, q, 2);
        const float m = s * (1.f / CH);
        const float var = fmaxf(fmaf(-m, m, q * (1.f / CH)), 0.f);
        float rs;
        asm("rsqrt.approx.ftz.f32 %0, %1;" : "=f"(rs) : "f"(var + 1e-5f));
        rs *= GA;
        const float nb = -m * rs;
#pragma unroll
        for (int i = 0; i < 12; i++) a[2 * i + r] = pack_h2(fmaf(v[2 * i], rs, nb), fmaf(v[2 * i + 1], rs, nb));
    }
}

__device__ __forceinline__ void epilogue(const acc2_t* acc, const uint32_t* res, uint32_t osc2, uint8_t* gp) {
#pragma unroll
    for (int r = 0; r < 2; r++)
#pragma unroll
        for (int i = 0; i < 3; i++) {
            uint32_t o[4];
#pragma unroll
            for (int jj = 0; jj < 4; jj++) {
                const uint32_t hv = acc[2 * (4 * i + jj) + r];
                const float2 f = __half22float2(*reinterpret_cast<const __half2*>(&hv));
                o[jj] = bfma(pack_b2(f.x, f.y), osc2, res[(r * 3 + i) * 4 + jj]);
            }
            stg128(gp + r * 8 * CH * 2 + i * 64, o[0], o[1], o[2], o[3]);
        }
}

struct Ctx {
    uint32_t H[2][CR];
    uint32_t a1[24];
    acc2_t acc[NACC2];
    uint32_t res[24];
};

template <int J>
__device__ __forceinline__ void phase(Ctx& c, bool first, bool last, uint32_t d1, uint32_t d2, uint32_t osc2,
                                      uint32_t cbase, int& cb, const uint8_t* xg, uint8_t* og, bool rel) {
    constexpr int P1 = (J == 0) ? 0 : (J == NCH - 1) ? P1LAST : P1MID;
    constexpr int P1PREV = (J == 1) ? 0 : (J == 0) ? P1LAST : P1MID;
    uint32_t* h = c.H[J & 1];
    wg_wait<NP - P1PREV>();
    pin<CR>(h);
    if (J == NCH - 1) {
        pin<24>(c.a1);
        if (!last) {
            bar_sync(BAR_FULL + cb, 256);
#pragma unroll
            for (int kk = 0; kk < 6; kk++) ldsm4(c.a1 + 4 * kk, cbase + cb * CBUF + kk * 32);
            if (rel) bar_arrive(BAR_EMPTY + cb, 256);
            cb += 2; if (cb >= NB) cb -= NB;
        }
        layernorm(c.a1);
    }
#pragma unroll
    for (int p = 0; p < NP; p++) {
#pragma unroll
        for (int i = 0; i < 4 * KSP; i++) h[p * 4 * KSP + i] = gelu2(h[p * 4 * KSP + i]);
        pin<4 * KSP>(h + p * 4 * KSP);
        if (p == P1) {
            wg_wait<P1>();
            if (J < NCH - 1) gemm1<(J + 1) % NCH>(c.H[(J + 1) & 1], c.a1, d1);
            else if (!last) gemm1<0>(c.H[0], c.a1, d1);
            else wg_commit();
            if (J == 0) {
                pin<NACC2>(c.acc);
                if (!first) epilogue(c.acc, c.res, osc2, og - 4 * IMG_W * CH * 2);
                pin<NACC2>(c.acc);
            }
            if (J == NCH - 1) {
#pragma unroll
                for (int r = 0; r < 2; r++)
#pragma unroll
                    for (int i = 0; i < 3; i++) ldg128(c.res + (r * 3 + i) * 4, xg + r * 8 * CH * 2 + i * 64);
            }
        }
        wg_fence();
#pragma unroll
        for (int k = 0; k < KSP; k++) {
            const int ks = p * KSP + k;
            if (J == 0 && ks == 0) gemm2_step<0>(c.acc, h + 4 * ks, d2, J * (CN / 16) + ks);
            else gemm2_step<1>(c.acc, h + 4 * ks, d2, J * (CN / 16) + ks);
        }
        wg_commit();
    }
}

__global__ void __launch_bounds__(384, 1)
replk_kernel(const __grid_constant__ CUtensorMap tmx, const uint8_t* __restrict__ x, const uint32_t* __restrict__ dwl,
             const uint32_t* __restrict__ dws, const uint8_t* __restrict__ w1, const uint8_t* __restrict__ w2,
             uint8_t* __restrict__ out) {
    extern __shared__ __align__(1024) uint8_t smem[];
    const uint32_t sb = (uint32_t)__cvta_generic_to_shared(smem);
    const int tid = threadIdx.x, lane = tid & 31;
    const int warp = __shfl_sync(0xffffffffu, tid >> 5, 0);
    const int w0 = (blockIdx.x % (IMG_W / SW)) * SW, y0 = (blockIdx.x / (IMG_W / SW)) * RB;

    if (warp >= 8) {
        asm volatile("setmaxnreg.dec.sync.aligned.u32 %0;" ::"n"(REG_CONV));
        const int cw = warp - 8;
        const uint32_t bar_full = sb + OFF_BAR, bar_empty = sb + OFF_BAR + 8 * NS;
        const bool prod = (tid == 256);
        if (prod) {
#pragma unroll
            for (int s = 0; s < NS; s++) { mbar_init(bar_full + 8 * s, 1); mbar_init(bar_empty + 8 * s, 4); }
            asm volatile("fence.mbarrier_init.release.cluster;" ::: "memory");
            asm volatile("fence.proxy.async.shared::cta;" ::: "memory");
#pragma unroll
            for (int s = 0; s < NS; s++) {
                mbar_expect_tx(bar_full + 8 * s, XSTG);
                tma_load3(sb + OFF_X + s * XSTG, &tmx, bar_full + 8 * s, 0, w0 - 2, y0 - 2 + 2 * s);
            }
        }
        const int hi = lane >> 4;
        const int wordA = (cw < 3) ? lane : 32 + (lane & 15);
        const int pxA = (cw < 3) ? 8 * cw : 16 * hi;
        const int wordB = (cw < 2) ? lane : 32 + (lane & 15);
        const int pxB = (cw < 2) ? 24 + 4 * cw : 16 * hi + 8 + 4 * (cw - 2);
        uint32_t wA[25], wB[25];
#pragma unroll
        for (int i = 0; i < 5; i++)
#pragma unroll
            for (int j = 0; j < 5; j++) {
                wA[i * 5 + j] = __ldg(dws + (i * 5 + j) * 48 + wordA);
                wB[i * 5 + j] = __ldg(dws + (i * 5 + j) * 48 + wordB);
                if (i >= 1 && i <= 3 && j >= 1 && j <= 3) {
                    wA[i * 5 + j] = badd(wA[i * 5 + j], __ldg(dwl + ((i - 1) * 3 + j - 1) * 48 + wordA));
                    wB[i * 5 + j] = badd(wB[i * 5 + j], __ldg(dwl + ((i - 1) * 3 + j - 1) * 48 + wordB));
                }
            }
        uint32_t accA[4][8], accB[4][4];
#pragma unroll
        for (int i = 0; i < 4; i++) {
#pragma unroll
            for (int p = 0; p < 8; p++) accA[i][p] = 0;
#pragma unroll
            for (int p = 0; p < 4; p++) accB[i][p] = 0;
        }
        const uint32_t xa0 = sb + OFF_X + pxA * (CH * 2) + wordA * 4;
        const uint32_t xb0 = sb + OFF_X + pxB * (CH * 2) + wordB * 4;
        const uint32_t oa0 = sb + OFF_C + (pxA >> 4) * CGRP + (pxA & 15) * CPITCH + wordA * 4;
        const uint32_t ob0 = sb + OFF_C + (pxB >> 4) * CGRP + (pxB & 15) * CPITCH + wordB * 4;
        bar_sync(BAR_CONS + 1, 128);
        int slot = 0, par = 0, cb = 0;
#pragma unroll 1
        for (int st = 0; st < NSTG; st++) {
            if (prod && st >= 1 && st - 1 + NS < NSTG) {
                const int ps = slot == 0 ? NS - 1 : slot - 1;
                mbar_wait(bar_empty + 8 * ps, slot == 0 ? par ^ 1 : par);
                mbar_expect_tx(bar_full + 8 * ps, XSTG);
                tma_load3(sb + OFF_X + ps * XSTG, &tmx, bar_full + 8 * ps, 0, w0 - 2, y0 - 2 + 2 * (st - 1 + NS));
            }
            __syncwarp();
            mbar_wait(bar_full + 8 * slot, par);
            if (st >= 2 + NB) bar_sync(BAR_EMPTY + cb, 256);
            const uint32_t xo = slot * XSTG, co = cb * CBUF;
#pragma unroll
            for (int r = 0; r < 2; r++) {
                uint32_t xa[12], xb[8];
#pragma unroll
                for (int p = 0; p < 12; p++) xa[p] = lds32(xa0 + xo + r * XROW + p * (CH * 2));
#pragma unroll
                for (int p = 0; p < 8; p++) xb[p] = lds32(xb0 + xo + r * XROW + p * (CH * 2));
                if (r == 1) {
                    __syncwarp();
                    if (lane == 0) mbar_arrive(bar_empty + 8 * slot);
                }
                conv_row<8>(xa, wA, accA, oa0 + co + r * 2 * CGRP);
                conv_row<4>(xb, wB, accB, ob0 + co + r * 2 * CGRP);
            }
            if (st >= 2) {
                bar_arrive(BAR_FULL + cb, 256);
                if (++cb == NB) cb = 0;
            }
            if (++slot == NS) { slot = 0; par ^= 1; }
        }
    } else {
        asm volatile("setmaxnreg.inc.sync.aligned.u32 %0;" ::"n"(REG_CONS));
        const int wg = warp >> 2, wq = warp & 3;
        uint32_t osc2;
        {
            uint32_t r1[18][4], r2[18][4];
            const int kr = lane & 7, nq = lane >> 3;
#pragma unroll
            for (int i = 0; i < 18; i++) {
                const int it = i * 8 + warp, kb = it / 12, n4 = it % 12;
                ldg128(r1[i], w1 + ((kb * 8 + kr) * HID + (n4 * 4 + nq) * 8) * 2);
            }
#pragma unroll
            for (int i = 0; i < 18; i++) {
                const int it = i * 8 + warp, kb = it / 3, n4 = it % 3;
                ldg128(r2[i], w2 + ((kb * 8 + kr) * CH + (n4 * 4 + nq) * 8) * 2);
            }
            uint32_t m1 = 0, m2 = 0;
#pragma unroll
            for (int i = 0; i < 18; i++) {
                const int it = i * 8 + warp, kb = it / 12, n4 = it % 12;
                uint32_t o[4];
#pragma unroll
                for (int j = 0; j < 4; j++) {
                    m1 = __vmaxu2(m1, r1[i][j] & 0x7fff7fffu);
                    o[j] = pack_h2(bf_lo(r1[i][j]), bf_hi(r1[i][j]));
                }
                sts128(sb + OFF_W1 + (kb * 48 + n4 * 4 + nq) * 128 + kr * 16, o[0], o[1], o[2], o[3]);
            }
#pragma unroll
            for (int i = 0; i < 18; i++)
#pragma unroll
                for (int j = 0; j < 4; j++) m2 = __vmaxu2(m2, r2[i][j] & 0x7fff7fffu);
            m1 = __reduce_max_sync(0xffffffffu, max(m1 >> 16, m1 & 0xffffu));
            m2 = __reduce_max_sync(0xffffffffu, max(m2 >> 16, m2 & 0xffffu));
            if (lane == 0) sts32(sb + OFF_RED + warp * 4, (m1 << 16) | m2);
            bar_sync(BAR_CONS, 256);
            uint32_t mm = lds32(sb + OFF_RED + (lane & 7) * 4);
            m1 = __reduce_max_sync(0xffffffffu, mm >> 16);
            m2 = __reduce_max_sync(0xffffffffu, mm & 0xffffu);
            const int e1 = (int)(m1 >> 7) - 127, e2 = (int)(m2 >> 7) - 127;
            int e = min(-3 - e1 - e2, 13 - e2);
            e = max(min(e, 100), -100);
            const float wsc = __uint_as_float((uint32_t)(127 + e) << 23) * INV2A;
            osc2 = ((uint32_t)(127 - e) << 7) * 0x10001u;
#pragma unroll
            for (int i = 0; i < 18; i++) {
                const int it = i * 8 + warp, kb = it / 3, n4 = it % 3;
#pragma unroll
                for (int j = 0; j < 4; j++)
                    sts32(sb + OFF_W2 + (kb * 12 + n4 * 4 + j) * 128 + kr * 16 + nq * 4,
                          pack_h2(bf_lo(r2[i][j]) * wsc, bf_hi(r2[i][j]) * wsc));
            }
            asm volatile("fence.proxy.async.shared::cta;" ::: "memory");
            bar_sync(BAR_CONS, 256);
        }
        const uint32_t d1 = (((sb + OFF_W1) & 0x3ffff) >> 4) | ((48 * 128 >> 4) << 16);
        const uint32_t d2 = (((sb + OFF_W2) & 0x3ffff) >> 4) | ((12 * 128 >> 4) << 16);
        const uint32_t cbase = sb + OFF_C + wq * CGRP + (lane & 15) * CPITCH + (lane >> 4) * 16;
        size_t goff = ((size_t)(y0 + 2 * wg + (wq >> 1)) * IMG_W + w0 + (wq & 1) * 16 + (lane >> 2)) * (CH * 2) + (lane & 3) * 16;
        const uint8_t* xg = x + goff;
        uint8_t* og = out + goff;
        Ctx c;
#pragma unroll
        for (int i = 0; i < NACC2; i++) c.acc[i] = 0;
#pragma unroll
        for (int i = 0; i < CR; i++) { c.H[0][i] = 0; c.H[1][i] = 0; }
#pragma unroll
        for (int i = 0; i < 24; i++) c.res[i] = 0;
        int cb = wg;
        bar_sync(BAR_FULL + cb, 256);
#pragma unroll
        for (int kk = 0; kk < 6; kk++) ldsm4(c.a1 + 4 * kk, cbase + cb * CBUF + kk * 32);
        bar_arrive(BAR_EMPTY + cb, 256);
        cb += 2; if (cb >= NB) cb -= NB;
        layernorm(c.a1);
        gemm1<0>(c.H[0], c.a1, d1);
#pragma unroll
        for (int i = 0; i < NP - P1LAST; i++) wg_commit();
#pragma unroll 1
        for (int i = 0; i < NT / 2; i++) {
            const bool first = (i == 0), last = (i == NT / 2 - 1);
            const bool rel = (2 * (i + 1) + wg + NB < NT);
            phase<0>(c, first, last, d1, d2, osc2, cbase, cb, xg, og, rel);
            phase<1>(c, first, last, d1, d2, osc2, cbase, cb, xg, og, rel);
            phase<2>(c, first, last, d1, d2, osc2, cbase, cb, xg, og, rel);
            phase<3>(c, first, last, d1, d2, osc2, cbase, cb, xg, og, rel);
            xg += 4 * IMG_W * CH * 2;
            og += 4 * IMG_W * CH * 2;
        }
        wg_wait<0>();
        pin<NACC2>(c.acc);
        epilogue(c.acc, c.res, osc2, og - 4 * IMG_W * CH * 2);
    }
}

typedef CUresult (*EncodeFn)(CUtensorMap*, CUtensorMapDataType, cuuint32_t, void*, const cuuint64_t*, const cuuint64_t*,
                             const cuuint32_t*, const cuuint32_t*, CUtensorMapInterleave, CUtensorMapSwizzle,
                             CUtensorMapL2promotion, CUtensorMapFloatOOBfill);

}

extern "C" void kernel_launch(void* const* d_in, const int* in_sizes, int n_in, void* d_out, int out_size) {
    static EncodeFn enc = nullptr;
    if (!enc) {
        void* fn = nullptr;
        cudaDriverEntryPointQueryResult qr;
        cudaGetDriverEntryPoint("cuTensorMapEncodeTiled", &fn, cudaEnableDefault, &qr);
        enc = (EncodeFn)fn;
        cudaFuncSetAttribute(replk_kernel, cudaFuncAttributeMaxDynamicSharedMemorySize, SMEM_BYTES);
    }
    CUtensorMap tm;
    const cuuint64_t gdim[3] = {CH, IMG_W, IMG_H};
    const cuuint64_t gstr[2] = {CH * 2, (cuuint64_t)IMG_W * CH * 2};
    const cuuint32_t box[3] = {CH, SW + 4, 2};
    const cuuint32_t estr[3] = {1, 1, 1};
    enc(&tm, CU_TENSOR_MAP_DATA_TYPE_BFLOAT16, 3, d_in[0], gdim, gstr, box, estr, CU_TENSOR_MAP_INTERLEAVE_NONE,
        CU_TENSOR_MAP_SWIZZLE_NONE, CU_TENSOR_MAP_L2_PROMOTION_L2_256B, CU_TENSOR_MAP_FLOAT_OOB_FILL_NONE);
    replk_kernel<<<(IMG_W / SW) * (IMG_H / RB), 384, SMEM_BYTES>>>(
        tm, (const uint8_t*)d_in[0], (const uint32_t*)d_in[1], (const uint32_t*)d_in[2], (const uint8_t*)d_in[3],
        (const uint8_t*)d_in[4], (uint8_t*)d_out);
}
```

```cpp
#include <cuda_runtime.h>
#include <cuda_bf16.h>
#include <cuda_fp16.h>
#include <cuda.h>
#include <stdint.h>

namespace {

constexpr int IMG_H = 512, IMG_W = 512, CH = 96, HID = 384;
constexpr int SW = 32;
constexpr int RB = 64;
constexpr int NT = RB / 2;
constexpr int NSTG = NT + 2;
constexpr int NS = 4;
constexpr int NB = 2;
#define REG_CONS 184
#define REG_CONV 136
#define CN 96
#define T0 12
#define EPI 2
#define LNCVT 0

constexpr int XROW = (SW + 4) * CH * 2;
constexpr int XSTG = 2 * XROW;
constexpr int CPITCH = 208;
constexpr int CGRP = 16 * CPITCH + 64;
constexpr int CBUF = 4 * CGRP;
constexpr int WBYTES = CH * HID * 2;
constexpr uint32_t SB = 1024;
constexpr uint32_t S_W1 = SB;
constexpr uint32_t S_W2 = S_W1 + WBYTES;
constexpr uint32_t S_X = S_W2 + WBYTES;
constexpr uint32_t S_C = S_X + NS * XSTG;
constexpr uint32_t S_BAR = S_C + NB * CBUF;
constexpr uint32_t S_WBAR = S_BAR + 8 * NS;
constexpr uint32_t S_RED = S_WBAR + 8 * 6;
constexpr int SMEM_BYTES = S_RED + 64 - SB;
static_assert(SMEM_BYTES <= 232448, "smem");

constexpr int NWG = 2;
constexpr int BAR_FULL = 1, BAR_EMPTY = 4, BAR_W = 6, BAR_RED = 7, BAR_TURN = 8, BAR_CV = 11, BAR_W1 = 12, BAR_W2 = 13;

constexpr float GA = 0.3292034911525734f;
constexpr uint32_t GK2 = 0x40d940d9u;
constexpr float INV2A = 1.5188174288475842f;
constexpr uint32_t WSC2 = (uint32_t)(127 - 48) * 0x00800080u;
constexpr float LN_EPS = 1e-5f * 0x1p-96f;
constexpr float LN_OUT = GA * 0x1p-112f;

constexpr uint32_t D1 = (S_W1 >> 4) | ((48 * 128 >> 4) << 16);
constexpr uint32_t D2 = (S_W2 >> 4) | ((12 * 128 >> 4) << 16);

template <int SCALE_D> __device__ __forceinline__ void wg_n64_h(uint32_t* d, const uint32_t* a, uint64_t desc);
template <>
__device__ __forceinline__ void wg_n64_h<0>(uint32_t* d, const uint32_t* a, uint64_t desc) {
    asm volatile("wgmma.mma_async.sync.aligned.m64n64k16.f16.f16.f16 {"
        "%0,%1,%2,%3,%4,%5,%6,%7,%8,%9,%10,%11,%12,%13,%14,%15},"
        "{%16,%17,%18,%19}, %20, 0, 1, 1, 1;"
        : "=r"(d[0]), "=r"(d[1]), "=r"(d[2]), "=r"(d[3]), "=r"(d[4]), "=r"(d[5]), "=r"(d[6]), "=r"(d[7]),
          "=r"(d[8]), "=r"(d[9]), "=r"(d[10]), "=r"(d[11]), "=r"(d[12]), "=r"(d[13]), "=r"(d[14]), "=r"(d[15])
        : "r"(a[0]), "r"(a[1]), "r"(a[2]), "r"(a[3]), "l"(desc));
}
template <>
__device__ __forceinline__ void wg_n64_h<1>(uint32_t* d, const uint32_t* a, uint64_t desc) {
    asm volatile("wgmma.mma_async.sync.aligned.m64n64k16.f16.f16.f16 {"
        "%0,%1,%2,%3,%4,%5,%6,%7,%8,%9,%10,%11,%12,%13,%14,%15},"
        "{%16,%17,%18,%19}, %20, 1, 1, 1, 1;"
        : "+r"(d[0]), "+r"(d[1]), "+r"(d[2]), "+r"(d[3]), "+r"(d[4]), "+r"(d[5]), "+r"(d[6]), "+r"(d[7]),
          "+r"(d[8]), "+r"(d[9]), "+r"(d[10]), "+r"(d[11]), "+r"(d[12]), "+r"(d[13]), "+r"(d[14]), "+r"(d[15])
        : "r"(a[0]), "r"(a[1]), "r"(a[2]), "r"(a[3]), "l"(desc));
}
template <int SCALE_D> __device__ __forceinline__ void wg_n96_h(uint32_t* d, const uint32_t* a, uint64_t desc);
template <>
__device__ __forceinline__ void wg_n96_h<0>(uint32_t* d, const uint32_t* a, uint64_t desc) {
    asm volatile("wgmma.mma_async.sync.aligned.m64n96k16.f16.f16.f16 {"
        "%0,%1,%2,%3,%4,%5,%6,%7,%8,%9,%10,%11,%12,%13,%14,%15,"
        "%16,%17,%18,%19,%20,%21,%22,%23},"
        "{%24,%25,%26,%27}, %28, 0, 1, 1, 1;"
        : "=r"(d[0]), "=r"(d[1]), "=r"(d[2]), "=r"(d[3]), "=r"(d[4]), "=r"(d[5]), "=r"(d[6]), "=r"(d[7]),
          "=r"(d[8]), "=r"(d[9]), "=r"(d[10]), "=r"(d[11]), "=r"(d[12]), "=r"(d[13]), "=r"(d[14]), "=r"(d[15]),
          "=r"(d[16]), "=r"(d[17]), "=r"(d[18]), "=r"(d[19]), "=r"(d[20]), "=r"(d[21]), "=r"(d[22]), "=r"(d[23])
        : "r"(a[0]), "r"(a[1]), "r"(a[2]), "r"(a[3]), "l"(desc));
}
template <>
__device__ __forceinline__ void wg_n96_h<1>(uint32_t* d, const uint32_t* a, uint64_t desc) {
    asm volatile("wgmma.mma_async.sync.aligned.m64n96k16.f16.f16.f16 {"
        "%0,%1,%2,%3,%4,%5,%6,%7,%8,%9,%10,%11,%12,%13,%14,%15,"
        "%16,%17,%18,%19,%20,%21,%22,%23},"
        "{%24,%25,%26,%27}, %28, 1, 1, 1, 1;"
        : "+r"(d[0]), "+r"(d[1]), "+r"(d[2]), "+r"(d[3]), "+r"(d[4]), "+r"(d[5]), "+r"(d[6]), "+r"(d[7]),
          "+r"(d[8]), "+r"(d[9]), "+r"(d[10]), "+r"(d[11]), "+r"(d[12]), "+r"(d[13]), "+r"(d[14]), "+r"(d[15]),
          "+r"(d[16]), "+r"(d[17]), "+r"(d[18]), "+r"(d[19]), "+r"(d[20]), "+r"(d[21]), "+r"(d[22]), "+r"(d[23])
        : "r"(a[0]), "r"(a[1]), "r"(a[2]), "r"(a[3]), "l"(desc));
}
template <int SCALE_D> __device__ __forceinline__ void wg_n128_h(uint32_t* d, const uint32_t* a, uint64_t desc);
template <>
__device__ __forceinline__ void wg_n128_h<0>(uint32_t* d, const uint32_t* a, uint64_t desc) {
    asm volatile("wgmma.mma_async.sync.aligned.m64n128k16.f16.f16.f16 {"
        "%0,%1,%2,%3,%4,%5,%6,%7,%8,%9,%10,%11,%12,%13,%14,%15,"
        "%16,%17,%18,%19,%20,%21,%22,%23,%24,%25,%26,%27,%28,%29,%30,%31},"
        "{%32,%33,%34,%35}, %36, 0, 1, 1, 1;"
        : "=r"(d[0]), "=r"(d[1]), "=r"(d[2]), "=r"(d[3]), "=r"(d[4]), "=r"(d[5]), "=r"(d[6]), "=r"(d[7]),
          "=r"(d[8]), "=r"(d[9]), "=r"(d[10]), "=r"(d[11]), "=r"(d[12]), "=r"(d[13]), "=r"(d[14]), "=r"(d[15]),
          "=r"(d[16]), "=r"(d[17]), "=r"(d[18]), "=r"(d[19]), "=r"(d[20]), "=r"(d[21]), "=r"(d[22]), "=r"(d[23]),
          "=r"(d[24]), "=r"(d[25]), "=r"(d[26]), "=r"(d[27]), "=r"(d[28]), "=r"(d[29]), "=r"(d[30]), "=r"(d[31])
        : "r"(a[0]), "r"(a[1]), "r"(a[2]), "r"(a[3]), "l"(desc));
}
template <>
__device__ __forceinline__ void wg_n128_h<1>(uint32_t* d, const uint32_t* a, uint64_t desc) {
    asm volatile("wgmma.mma_async.sync.aligned.m64n128k16.f16.f16.f16 {"
        "%0,%1,%2,%3,%4,%5,%6,%7,%8,%9,%10,%11,%12,%13,%14,%15,"
        "%16,%17,%18,%19,%20,%21,%22,%23,%24,%25,%26,%27,%28,%29,%30,%31},"
        "{%32,%33,%34,%35}, %36, 1, 1, 1, 1;"
        : "+r"(d[0]), "+r"(d[1]), "+r"(d[2]), "+r"(d[3]), "+r"(d[4]), "+r"(d[5]), "+r"(d[6]), "+r"(d[7]),
          "+r"(d[8]), "+r"(d[9]), "+r"(d[10]), "+r"(d[11]), "+r"(d[12]), "+r"(d[13]), "+r"(d[14]), "+r"(d[15]),
          "+r"(d[16]), "+r"(d[17]), "+r"(d[18]), "+r"(d[19]), "+r"(d[20]), "+r"(d[21]), "+r"(d[22]), "+r"(d[23]),
          "+r"(d[24]), "+r"(d[25]), "+r"(d[26]), "+r"(d[27]), "+r"(d[28]), "+r"(d[29]), "+r"(d[30]), "+r"(d[31])
        : "r"(a[0]), "r"(a[1]), "r"(a[2]), "r"(a[3]), "l"(desc));
}
template <int SCALE_D> __device__ __forceinline__ void wg_n192_h(uint32_t* d, const uint32_t* a, uint64_t desc);
template <>
__device__ __forceinline__ void wg_n192_h<0>(uint32_t* d, const uint32_t* a, uint64_t desc) {
    asm volatile("wgmma.mma_async.sync.aligned.m64n192k16.f16.f16.f16 {"
        "%0,%1,%2,%3,%4,%5,%6,%7,%8,%9,%10,%11,%12,%13,%14,%15,"
        "%16,%17,%18,%19,%20,%21,%22,%23,%24,%25,%26,%27,%28,%29,%30,%31,"
        "%32,%33,%34,%35,%36,%37,%38,%39,%40,%41,%42,%43,%44,%45,%46,%47},"
        "{%48,%49,%50,%51}, %52, 0, 1, 1, 1;"
        : "=r"(d[0]), "=r"(d[1]), "=r"(d[2]), "=r"(d[3]), "=r"(d[4]), "=r"(d[5]), "=r"(d[6]), "=r"(d[7]),
          "=r"(d[8]), "=r"(d[9]), "=r"(d[10]), "=r"(d[11]), "=r"(d[12]), "=r"(d[13]), "=r"(d[14]), "=r"(d[15]),
          "=r"(d[16]), "=r"(d[17]), "=r"(d[18]), "=r"(d[19]), "=r"(d[20]), "=r"(d[21]), "=r"(d[22]), "=r"(d[23]),
          "=r"(d[24]), "=r"(d[25]), "=r"(d[26]), "=r"(d[27]), "=r"(d[28]), "=r"(d[29]), "=r"(d[30]), "=r"(d[31]),
          "=r"(d[32]), "=r"(d[33]), "=r"(d[34]), "=r"(d[35]), "=r"(d[36]), "=r"(d[37]), "=r"(d[38]), "=r"(d[39]),
          "=r"(d[40]), "=r"(d[41]), "=r"(d[42]), "=r"(d[43]), "=r"(d[44]), "=r"(d[45]), "=r"(d[46]), "=r"(d[47])
        : "r"(a[0]), "r"(a[1]), "r"(a[2]), "r"(a[3]), "l"(desc));
}
template <>
__device__ __forceinline__ void wg_n192_h<1>(uint32_t* d, const uint32_t* a, uint64_t desc) {
    asm volatile("wgmma.mma_async.sync.aligned.m64n192k16.f16.f16.f16 {"
        "%0,%1,%2,%3,%4,%5,%6,%7,%8,%9,%10,%11,%12,%13,%14,%15,"
        "%16,%17,%18,%19,%20,%21,%22,%23,%24,%25,%26,%27,%28,%29,%30,%31,"
        "%32,%33,%34,%35,%36,%37,%38,%39,%40,%41,%42,%43,%44,%45,%46,%47},"
        "{%48,%49,%50,%51}, %52, 1, 1, 1, 1;"
        : "+r"(d[0]), "+r"(d[1]), "+r"(d[2]), "+r"(d[3]), "+r"(d[4]), "+r"(d[5]), "+r"(d[6]), "+r"(d[7]),
          "+r"(d[8]), "+r"(d[9]), "+r"(d[10]), "+r"(d[11]), "+r"(d[12]), "+r"(d[13]), "+r"(d[14]), "+r"(d[15]),
          "+r"(d[16]), "+r"(d[17]), "+r"(d[18]), "+r"(d[19]), "+r"(d[20]), "+r"(d[21]), "+r"(d[22]), "+r"(d[23]),
          "+r"(d[24]), "+r"(d[25]), "+r"(d[26]), "+r"(d[27]), "+r"(d[28]), "+r"(d[29]), "+r"(d[30]), "+r"(d[31]),
          "+r"(d[32]), "+r"(d[33]), "+r"(d[34]), "+r"(d[35]), "+r"(d[36]), "+r"(d[37]), "+r"(d[38]), "+r"(d[39]),
          "+r"(d[40]), "+r"(d[41]), "+r"(d[42]), "+r"(d[43]), "+r"(d[44]), "+r"(d[45]), "+r"(d[46]), "+r"(d[47])
        : "r"(a[0]), "r"(a[1]), "r"(a[2]), "r"(a[3]), "l"(desc));
}

__device__ __forceinline__ void wg_fence() { asm volatile("wgmma.fence.sync.aligned;" ::: "memory"); }
__device__ __forceinline__ void wg_commit() { asm volatile("wgmma.commit_group.sync.aligned;" ::: "memory"); }
template <int N> __device__ __forceinline__ void wg_wait() { asm volatile("wgmma.wait_group.sync.aligned %0;" ::"n"(N) : "memory"); }
template <int N> __device__ __forceinline__ void pin(uint32_t* r) {
#pragma unroll
    for (int i = 0; i < N; i++) asm volatile("" : "+r"(r[i])::"memory");
}
__device__ __forceinline__ void sbar() { asm volatile("griddepcontrol.launch_dependents;" ::: "memory"); }

__device__ __forceinline__ void bar_sync(int id, int n) { asm volatile("bar.sync %0, %1;" ::"r"(id), "r"(n) : "memory"); }
__device__ __forceinline__ void bar_arrive(int id, int n) { asm volatile("bar.arrive %0, %1;" ::"r"(id), "r"(n) : "memory"); }
__device__ __forceinline__ void mbar_init(uint32_t a, uint32_t cnt) { asm volatile("mbarrier.init.shared::cta.b64 [%0], %1;" ::"r"(a), "r"(cnt) : "memory"); }
__device__ __forceinline__ void mbar_expect_tx(uint32_t a, uint32_t bytes) { asm volatile("mbarrier.arrive.expect_tx.shared::cta.b64 _, [%0], %1;" ::"r"(a), "r"(bytes) : "memory"); }
__device__ __forceinline__ bool mbar_try(uint32_t a, uint32_t parity) {
    uint32_t ok;
    asm volatile("{.reg .pred p; mbarrier.try_wait.parity.shared::cta.b64 p, [%1], %2; selp.u32 %0, 1, 0, p;}" : "=r"(ok) : "r"(a), "r"(parity) : "memory");
    return ok;
}
__device__ __forceinline__ void mbar_wait(uint32_t a, uint32_t parity) {
    asm volatile("{.reg .pred p, q; .reg .u32 g; mov.u32 g, 0;\n"
                 "L: mbarrier.try_wait.parity.shared::cta.b64 p, [%0], %1;\n"
                 "add.u32 g, g, 1; setp.lt.and.u32 q, g, 0x400000, !p; @q bra L;}" ::"r"(a), "r"(parity) : "memory");
}
__device__ __forceinline__ bool mbar_test(uint32_t a, uint32_t parity) {
    uint32_t ok;
    asm volatile("{.reg .pred p; mbarrier.test_wait.parity.shared::cta.b64 p, [%1], %2; selp.u32 %0, 1, 0, p;}" : "=r"(ok) : "r"(a), "r"(parity) : "memory");
    return ok;
}
__device__ __forceinline__ bool elect() {
    uint32_t ok;
    asm volatile("{.reg .pred p; elect.sync _|p, 0xffffffff; selp.u32 %0, 1, 0, p;}" : "=r"(ok));
    return ok;
}
__device__ __forceinline__ void tma_x(const CUtensorMap* tm, int stage, int w0, int y0) {
    const uint32_t slot = stage & (NS - 1), bar = S_BAR + 8 * slot;
    mbar_expect_tx(bar, XSTG);
    asm volatile("cp.async.bulk.tensor.3d.shared::cluster.global.mbarrier::complete_tx::bytes [%0], [%1, {%3, %4, %5}], [%2];"
                 ::"r"(S_X + slot * XSTG), "l"(tm), "r"(bar), "r"(0), "r"(w0 - 2), "r"(y0 - 2 + 2 * stage) : "memory");
}
__device__ __forceinline__ void bulk_load(uint32_t dst, const void* src, uint32_t bytes, uint32_t bar) {
    asm volatile("cp.async.bulk.shared::cluster.global.mbarrier::complete_tx::bytes [%0], [%1], %2, [%3];"
                 ::"r"(dst), "l"(src), "r"(bytes), "r"(bar) : "memory");
}
__device__ __forceinline__ uint32_t lds32(uint32_t a) { uint32_t v; asm volatile("ld.shared.b32 %0, [%1];" : "=r"(v) : "r"(a)); return v; }
__device__ __forceinline__ void lds128(uint32_t* r, uint32_t a) { asm volatile("ld.shared.v4.b32 {%0,%1,%2,%3}, [%4];" : "=r"(r[0]), "=r"(r[1]), "=r"(r[2]), "=r"(r[3]) : "r"(a)); }
__device__ __forceinline__ void sts32(uint32_t a, uint32_t v) { asm volatile("st.shared.b32 [%0], %1;" ::"r"(a), "r"(v)); }
__device__ __forceinline__ void sts128(uint32_t a, uint32_t x, uint32_t y, uint32_t z, uint32_t w) { asm volatile("st.shared.v4.b32 [%0], {%1,%2,%3,%4};" ::"r"(a), "r"(x), "r"(y), "r"(z), "r"(w)); }
__device__ __forceinline__ void ldsm4(uint32_t* r, uint32_t a) {
    asm volatile("ldmatrix.sync.aligned.m8n8.x4.shared.b16 {%0,%1,%2,%3}, [%4];" : "=r"(r[0]), "=r"(r[1]), "=r"(r[2]), "=r"(r[3]) : "r"(a));
}
__device__ __forceinline__ void ldsm4s(uint32_t& r0, uint32_t& r1, uint32_t& r2, uint32_t& r3, uint32_t a) {
    asm volatile("ldmatrix.sync.aligned.m8n8.x4.shared.b16 {%0,%1,%2,%3}, [%4];" : "=r"(r0), "=r"(r1), "=r"(r2), "=r"(r3) : "r"(a));
}
__device__ __forceinline__ void ldsm2s(uint32_t& r0, uint32_t& r1, uint32_t a) {
    asm volatile("ldmatrix.sync.aligned.m8n8.x2.shared.b16 {%0,%1}, [%2];" : "=r"(r0), "=r"(r1) : "r"(a));
}
__device__ __forceinline__ void stsm4(uint32_t a, const uint32_t* r) {
    asm volatile("stmatrix.sync.aligned.m8n8.x4.shared.b16 [%4], {%0,%1,%2,%3};" ::"r"(r[0]), "r"(r[1]), "r"(r[2]), "r"(r[3]), "r"(a));
}
__device__ __forceinline__ void ldg128(uint32_t* r, const void* p) {
    asm volatile("ld.global.nc.L1::no_allocate.v4.b32 {%0,%1,%2,%3}, [%4];" : "=r"(r[0]), "=r"(r[1]), "=r"(r[2]), "=r"(r[3]) : "l"(p));
}
__device__ __forceinline__ void stg128(void* p, uint32_t x, uint32_t y, uint32_t z, uint32_t w) {
    asm volatile("st.global.L1::no_allocate.v4.b32 [%0], {%1,%2,%3,%4};" ::"l"(p), "r"(x), "r"(y), "r"(z), "r"(w));
}
__device__ __forceinline__ uint32_t bfma(uint32_t a, uint32_t b, uint32_t c) { uint32_t d; asm("fma.rn.bf16x2 %0, %1, %2, %3;" : "=r"(d) : "r"(a), "r"(b), "r"(c)); return d; }
__device__ __forceinline__ uint32_t bmul(uint32_t a, uint32_t b) { uint32_t d; asm("mul.rn.bf16x2 %0, %1, %2;" : "=r"(d) : "r"(a), "r"(b)); return d; }
__device__ __forceinline__ uint32_t vfma(uint32_t a, uint32_t b, uint32_t c) { uint32_t d; asm volatile("fma.rn.bf16x2 %0, %1, %2, %3;" : "=r"(d) : "r"(a), "r"(b), "r"(c)); return d; }
__device__ __forceinline__ void vacc(uint32_t& d, uint32_t a, uint32_t b) { asm volatile("fma.rn.bf16x2 %0, %1, %2, %0;" : "+r"(d) : "r"(a), "r"(b)); }
__device__ __forceinline__ uint32_t vmul(uint32_t a, uint32_t b) { uint32_t d; asm volatile("mul.rn.bf16x2 %0, %1, %2;" : "=r"(d) : "r"(a), "r"(b)); return d; }
__device__ __forceinline__ uint32_t badd(uint32_t a, uint32_t b) { uint32_t d; asm("add.rn.bf16x2 %0, %1, %2;" : "=r"(d) : "r"(a), "r"(b)); return d; }
__device__ __forceinline__ uint32_t habsmax(uint32_t m, uint32_t a, uint32_t b) { return __vimax3_u16x2(m, a & 0x7fff7fffu, b & 0x7fff7fffu); }
__device__ __forceinline__ float bf_lo(uint32_t v) { uint32_t d; asm("prmt.b32 %0, %1, 0, 0x1044;" : "=r"(d) : "r"(v)); return __uint_as_float(d); }
__device__ __forceinline__ float bf_hi(uint32_t v) { return __uint_as_float(v & 0xffff0000u); }
__device__ __forceinline__ uint32_t pack_h2(float lo, float hi) { uint32_t d; asm("cvt.rn.f16x2.f32 %0, %1, %2;" : "=r"(d) : "f"(hi), "f"(lo)); return d; }
__device__ __forceinline__ uint32_t pack_b2(float lo, float hi) { uint32_t d; asm("cvt.rn.bf16x2.f32 %0, %1, %2;" : "=r"(d) : "f"(hi), "f"(lo)); return d; }

template <int N> __device__ __forceinline__ void gelu(uint32_t* h) {
#pragma unroll
    for (int i = 0; i < N; i++) {
        uint32_t p, u, t;
        asm("fma.rn.f16x2 %0, %1, %1, %2;" : "=r"(p) : "r"(h[i]), "r"(GK2));
        asm("mul.rn.f16x2 %0, %1, %2;" : "=r"(u) : "r"(h[i]), "r"(p));
        asm("tanh.approx.f16x2 %0, %1;" : "=r"(t) : "r"(u));
        asm("fma.rn.f16x2 %0, %1, %2, %1;" : "=r"(h[i]) : "r"(h[i]), "r"(t));
    }
    pin<N>(h);
}
template <int N> __device__ __forceinline__ void gelu_a(uint32_t* t, const uint32_t* h) {
#pragma unroll
    for (int i = 0; i < N; i++) {
        uint32_t p, u;
        asm("fma.rn.f16x2 %0, %1, %1, %2;" : "=r"(p) : "r"(h[i]), "r"(GK2));
        asm("mul.rn.f16x2 %0, %1, %2;" : "=r"(u) : "r"(h[i]), "r"(p));
        asm("tanh.approx.f16x2 %0, %1;" : "=r"(t[i]) : "r"(u));
    }
    pin<N>(t);
}
template <int N> __device__ __forceinline__ void gelu_b(uint32_t* h, const uint32_t* t) {
#pragma unroll
    for (int i = 0; i < N; i++) asm volatile("fma.rn.f16x2 %0, %1, %2, %1;" : "=r"(h[i]) : "r"(h[i]), "r"(t[i]));
}
#define RESCARRY 3
#define MIDW 12
#define OV 1
#define SB2 SB1
#define SB3 SB1
#define SB1 { uint32_t ck; asm volatile("mov.u32 %0, %%clock;" : "=r"(ck)::"memory"); sink ^= ck; }

#define PEEL0 1
#define PEEL1 1
#define CFT 1
#define CORDER 1
template <int S, int P, int ILO, int IHI>
__device__ __forceinline__ void conv_col(uint32_t x, const uint32_t* w, uint32_t (&acc)[4][S], uint32_t (&o)[S]) {
#pragma unroll
    for (int j = 4; j >= 0; j--) {
        const int q = P - j;
        if (q < 0 || q >= S) continue;
#pragma unroll
        for (int i = IHI; i >= ILO; i--) {
            uint32_t& d = (i == 4) ? o[q] : acc[i == 4 ? 0 : 3 - i][q];
            const uint32_t ww = w[2 * (i * 5 + j)];
            if (j > 0) vacc(d, x, ww);
            else if (i == 4 && CORDER == 1) { d = acc[0][q]; vacc(d, x, ww); }
            else d = (i == 0) ? vmul(x, ww) : vfma(x, ww, acc[i == 0 ? 0 : 4 - i][q]);
        }
    }
}
#define CFENCE 0x5e
struct Conv {
    uint32_t w[50];
    uint32_t accA[4][8], accB[4][4];
    uint32_t sink;
    uint32_t xa[12], xb[8];
};
template <int K> __device__ __forceinline__ void conv_ld(Conv& c, uint32_t a1) { ldsm4s(c.xa[2 * K + 2], c.xb[2 * K], c.xa[2 * K + 3], c.xb[2 * K + 1], a1 + K * 2 * CH * 2); }
template <int ILO, int IHI, bool NEXT, typename Fn, typename Fm, typename Fk>
__device__ __forceinline__ void conv_row(Conv& c, uint32_t a1, uint32_t a2, uint32_t sA, uint32_t sB, Fn before_store, Fm after_store, Fk late) {
    uint32_t oA[8], oB[4];
#define FN(n) { if ((CFENCE >> n) & 1) { uint32_t ck; asm volatile("mov.u32 %0, %%clock;" : "=r"(ck)::"memory"); c.sink ^= ck; } }
    constexpr int IH = IHI == 4 ? 3 : IHI;
#define CA(p) conv_col<8, p, 4, 4>(c.xa[p], c.w + 1, c.accA, oA)
#define CB(p) conv_col<4, p, 4, 4>(c.xb[p], c.w, c.accB, oB)
    if (IHI == 4) {
        CA(0); CA(1); CA(2); CB(0); CA(3); CB(1); CA(4); CB(2); CA(5); CB(3); CA(6); CB(4); CA(7); CB(5);
        before_store();
        stsm4(sA, oA);
        CA(8); CB(6); CA(9); CB(7); CA(10); CA(11);
        stsm4(sB, oB);
        stsm4(sA + 4 * CPITCH, oA + 4);
        after_store();
        FN(6)
    }
#undef CA
#undef CB
#define CA(p) conv_col<8, p, ILO, IH>(c.xa[p], c.w + 1, c.accA, oA)
#define CB(p) conv_col<4, p, ILO, IH>(c.xb[p], c.w, c.accB, oB)
    CA(0); CA(1); FN(0)
    if (NEXT) ldsm2s(c.xa[0], c.xa[1], a2);
    CA(2); CB(0); CA(3); CB(1); FN(1)
    if (NEXT) conv_ld<0>(c, a1);
    CA(4); CB(2); CA(5); CB(3); FN(2)
    if (NEXT) conv_ld<1>(c, a1);
    CA(6); CB(4); CA(7); CB(5); FN(3)
    if (NEXT) conv_ld<2>(c, a1);
    if (IH == 4) { before_store(); stsm4(sA, oA); }
    late();
    CA(8); CB(6); CA(9); CB(7); FN(4)
    if (NEXT) conv_ld<3>(c, a1);
    if (IH == 4) stsm4(sB, oB);
    CA(10); CA(11); FN(5)
    if (NEXT) ldsm2s(c.xa[10], c.xa[11], a2 + 10 * CH * 2);
    if (IH == 4) { stsm4(sA + 4 * CPITCH, oA + 4); after_store(); }
#undef FN
#undef CA
#undef CB
}

__device__ __forceinline__ uint64_t mkd(uint64_t db, uint32_t lo) { uint64_t d; asm volatile("add.u64 %0, %1, %2;" : "=l"(d) : "l"(db), "l"((uint64_t)lo)); return d; }
template <int J, int K0, int K1> __device__ __forceinline__ void gemm1(uint32_t* H, const uint32_t* a1, uint64_t db) {
#pragma unroll
    for (int kk = K0; kk < K1; kk++) {
        const uint64_t d = mkd(db, D1 + ((2 * kk * 48 + J * (CN / 8)) * 128 >> 4));
        if (kk == 0) wg_n96_h<0>(H + J * 24, a1, d);
        else wg_n96_h<1>(H + J * 24, a1 + 4 * kk, d);
    }
}
template <int K0, int K1> __device__ __forceinline__ void gemm2(uint32_t* acc, const uint32_t* H, uint64_t db) {
#pragma unroll
    for (int ks = K0; ks < K1; ks++) {
        const uint64_t d = mkd(db, D2 + (2 * ks * 12 * 128 >> 4));
        if (ks == 0) wg_n96_h<0>(acc, H, d);
        else wg_n96_h<1>(acc, H + 4 * ks, d);
    }
}

__device__ __forceinline__ float quad_sum(uint32_t v) {
    float s = bf_lo(v) + bf_hi(v);
    s += __shfl_xor_sync(0xffffffffu, s, 1);
    s += __shfl_xor_sync(0xffffffffu, s, 2);
    return s;
}
__device__ __forceinline__ void ln_mean(const uint32_t* a, uint32_t* st) {
#pragma unroll
    for (int r = 0; r < 2; r++) {
        uint32_t s[6];
#pragma unroll
        for (int i = 0; i < 6; i++) s[i] = badd(a[4 * i + r], a[4 * i + 2 + r]);
        const uint32_t t = badd(badd(badd(s[0], s[1]), badd(s[2], s[3])), badd(s[4], s[5]));
        const float m = quad_sum(t) * (-1.f / CH);
        st[r] = pack_b2(m, m);
    }
    pin<2>(st);
}
template <int r> __device__ __forceinline__ void ln_var(uint32_t* a, uint32_t* st) {
    uint32_t q[3];
#pragma unroll
    for (int i = 0; i < 12; i++) {
        a[2 * i + r] = badd(a[2 * i + r], st[r]);
        q[i % 3] = (i < 3) ? bmul(a[2 * i + r], a[2 * i + r]) : bfma(a[2 * i + r], a[2 * i + r], q[i % 3]);
        pin<1>(a + 2 * i + r);
    }
    const float v = fmaf(quad_sum(badd(badd(q[0], q[1]), q[2])), 1.f / CH, LN_EPS);
    float rs;
    asm("rsqrt.approx.ftz.f32 %0, %1;" : "=f"(rs) : "f"(v));
    rs *= LN_OUT;
    st[r] = pack_b2(rs, rs);
    pin<1>(st + r);
}
template <int I0, int I1> __device__ __forceinline__ void ln_out(uint32_t* a, const uint32_t* b, const uint32_t* st) {
#pragma unroll
    for (int i = I0; i < I1; i++) {
        const uint32_t v = bmul(b[i], st[i & 1]);
        a[i] = v + 7u * (v & 0x7fff7fffu);
        pin<1>(a + i);
    }
}

__device__ __forceinline__ void epi_cvt(uint32_t* e, const uint32_t* acc) {
#pragma unroll
    for (int i = 0; i < 24; i++) {
        const uint32_t hv = acc[i];
        const float2 f = __half22float2(*reinterpret_cast<const __half2*>(&hv));
        e[i] = pack_b2(f.x, f.y);
    }
    pin<24>(e);
}
template <int R> __device__ __forceinline__ void epi_out(const uint32_t* e, const uint32_t* res, uint32_t osc2, uint8_t* gp, bool on) {
#pragma unroll
    for (int i = 0; i < 3; i++) {
        uint32_t o[4];
#pragma unroll
        for (int jj = 0; jj < 4; jj++) o[jj] = vfma(e[2 * (4 * i + jj) + R], osc2, res[(R * 3 + i) * 4 + jj]);
        asm volatile("{.reg .pred p; setp.ne.u32 p, %5, 0; @p st.global.L1::no_allocate.v4.b32 [%0], {%1,%2,%3,%4};}"
                     ::"l"(gp + R * 8 * CH * 2 + i * 64), "r"(o[0]), "r"(o[1]), "r"(o[2]), "r"(o[3]), "r"((uint32_t)on));
    }
}
template <int R> __device__ __forceinline__ void load_res(uint32_t* res, const uint8_t* xg) {
#pragma unroll
    for (int i = 0; i < 3; i++) ldg128(res + (R * 3 + i) * 4, xg + R * 8 * CH * 2 + i * 64);
}

#define TLREC(role, idx)
#define TLRECG(role, idx)

constexpr int TSTEP = 2 * NWG * IMG_W * CH * 2;

__global__ void __launch_bounds__(384, 1)
replk_kernel(const __grid_constant__ CUtensorMap tmx, const uint8_t* __restrict__ x, const uint8_t* __restrict__ dwl,
             const uint8_t* __restrict__ dws, const uint8_t* __restrict__ w1, const uint8_t* __restrict__ w2,
             uint8_t* __restrict__ out, const uint64_t db) {
    extern __shared__ __align__(1024) uint8_t smem[];
    const int tid = threadIdx.x, lane = tid & 31;
    const int warp = __shfl_sync(0xffffffffu, tid >> 5, 0);
    const int w0 = (blockIdx.x % (IMG_W / SW)) * SW, y0 = (blockIdx.x / (IMG_W / SW)) * RB;
    if (warp < 8) { TLREC(warp >> 2, 0); TLRECG(warp >> 2, 78); }
    if (warp == 0 && elect()) {
        if ((uint32_t)__cvta_generic_to_shared(smem) != SB) __trap();
#pragma unroll
        for (int s = 0; s < NS + 6; s++) mbar_init(S_BAR + 8 * s, 1);
        asm volatile("fence.mbarrier_init.release.cluster;" ::: "memory");
        TLREC(3, 43);
        mbar_expect_tx(S_WBAR + 40, 34 * CH * 2);
        bulk_load(S_C, dws, 25 * CH * 2, S_WBAR + 40);
        bulk_load(S_C + 25 * CH * 2, dwl, 9 * CH * 2, S_WBAR + 40);
        TLREC(3, 44);
        tma_x(&tmx, 0, w0, y0);
        tma_x(&tmx, 1, w0, y0);
        tma_x(&tmx, 2, w0, y0);
#pragma unroll
        for (int i = 0; i < 3; i++) {
            mbar_expect_tx(S_WBAR + 8 * i, WBYTES / 3);
            bulk_load(S_W1 + i * (WBYTES / 3), w1 + i * (WBYTES / 3), WBYTES / 3, S_WBAR + 8 * i);
            if (i == 0) tma_x(&tmx, 3, w0, y0);
        }
#pragma unroll
        for (int i = 0; i < 2; i++) {
            mbar_expect_tx(S_WBAR + 24 + 8 * i, WBYTES / 2);
            bulk_load(S_W2 + i * (WBYTES / 2), w2 + i * (WBYTES / 2), WBYTES / 2, S_WBAR + 24 + 8 * i);
        }
        TLREC(3, 45);
    }
    __syncthreads();
    if (warp == 8) TLREC(3, 46);

    if (warp >= 8) {
        asm volatile("setmaxnreg.dec.sync.aligned.u32 %0;" ::"n"(REG_CONV));
        const int cw = warp - 8;
        Conv c;
        {
            const uint32_t wsA = S_C + ((cw < 3) ? lane : 32 + (lane & 15)) * 4;
            const uint32_t wsB = S_C + ((cw < 2) ? lane : 32 + (lane & 15)) * 4;
            TLREC(3, 47);
            mbar_wait(S_WBAR + 40, 0);
            TLREC(3, 40);
            uint32_t t[52];
#pragma unroll
            for (int i = 0; i < 5; i++)
#pragma unroll
                for (int j = 0; j < 5; j++) {
                    uint32_t wa = lds32(wsA + (i * 5 + j) * CH * 2), wb = lds32(wsB + (i * 5 + j) * CH * 2);
                    if (i >= 1 && i <= 3 && j >= 1 && j <= 3) {
                        wa = badd(wa, lds32(wsA + (25 + (i - 1) * 3 + j - 1) * CH * 2));
                        wb = badd(wb, lds32(wsB + (25 + (i - 1) * 3 + j - 1) * CH * 2));
                    }
                    t[2 * (i * 5 + j)] = bmul(wb, WSC2);
                    t[2 * (i * 5 + j) + 1] = bmul(wa, WSC2);
                }
            t[50] = t[51] = 0;
            bar_sync(BAR_CV, 128);
            const uint32_t sc = S_C + (tid - 256) * 16;
#pragma unroll
            for (int k = 0; k < 13; k++) sts128(sc + k * 2048, t[4 * k], t[4 * k + 1], t[4 * k + 2], t[4 * k + 3]);
#pragma unroll
            for (int k = 0; k < 12; k++) lds128(c.w + 4 * k, sc + k * 2048);
            asm volatile("ld.shared.v2.b32 {%0,%1}, [%2];" : "=r"(c.w[48]), "=r"(c.w[49]) : "r"(sc + 12 * 2048));
            bar_sync(BAR_CV, 128);
        }
#pragma unroll
        for (int i = 0; i < 4; i++) {
#pragma unroll
            for (int p = 0; p < 8; p++) c.accA[i][p] = 0;
#pragma unroll
            for (int p = 0; p < 4; p++) c.accB[i][p] = 0;
        }
        const int mi = lane >> 3, qd = lane & 7;
        const int chA = (cw < 3) ? qd : 8 + (qd & 3), pxA = (cw < 3) ? 8 * cw : 16 * (qd >> 2);
        const int chB = (cw < 2) ? qd : 8 + (qd & 3), pxB = (cw < 2) ? 24 + 4 * cw : 16 * (qd >> 2) + 8 + 4 * (cw - 2);
        const uint32_t a1 = S_X + ((mi & 1) ? (pxB + (mi >> 1)) * (CH * 2) + chB * 16 : (pxA + 2 + (mi >> 1)) * (CH * 2) + chA * 16);
        const uint32_t a2 = S_X + (pxA + (mi & 1)) * (CH * 2) + chA * 16;
        const uint32_t sA = S_C + (pxA >> 4) * CGRP + ((pxA & 15) + mi) * CPITCH + chA * 16;
        const uint32_t sB = S_C + (pxB >> 4) * CGRP + ((pxB & 15) + mi) * CPITCH + chB * 16;
        auto nop = [] {};
        c.sink = lane;
        TLREC(3, 1);
        mbar_wait(S_BAR, 0);
        ldsm2s(c.xa[0], c.xa[1], a2);
        conv_ld<0>(c, a1); conv_ld<1>(c, a1); conv_ld<2>(c, a1); conv_ld<3>(c, a1);
        ldsm2s(c.xa[10], c.xa[11], a2 + 10 * CH * 2);
        TLREC(3, 41);
        conv_row<0, 0, true>(c, a1 + XROW, a2 + XROW, 0, 0, nop, nop, nop);
        mbar_wait(S_BAR + 8, 0);
        TLREC(3, 42);
        conv_row<0, 1, true>(c, a1 + XSTG, a2 + XSTG, 0, 0, nop, nop, nop);
        conv_row<0, 2, true>(c, a1 + XSTG + XROW, a2 + XSTG + XROW, 0, 0, nop, nop, nop);
        mbar_wait(S_BAR + 16, 0);
        int st = PEEL0;
        int fw = BAR_FULL + (PEEL0 + 2 * NWG - 2) % NWG;
        constexpr int LAST_ST = NSTG - 2 - PEEL1;
#pragma unroll 1
        for (;;) {
            const uint32_t xo = ((st + 1) & (NS - 1)) * XSTG, co = (st & 1) * CBUF;
            conv_row<0, 4, true>(c, a1 + xo, a2 + xo, sA + co + 2 * CGRP, sB + co + 2 * CGRP, nop,
                                 [&] { if (st >= 2) bar_arrive(fw, 256); }, nop);
            fw = fw == BAR_FULL + NWG - 1 ? BAR_FULL : fw + 1;
            TLREC(3, 2 + st);
            const uint32_t nb = S_BAR + 8 * ((st + 2) & (NS - 1)), np = ((st + 2) / NS) & 1;
            bool ok;
            conv_row<0, 4, true>(c, a1 + xo + XROW, a2 + xo + XROW, sA + CBUF - co, sB + CBUF - co,
                                 [&] { if (st >= 1 + NB) bar_sync(BAR_EMPTY + ((st + 1) & 1), 256); }, nop,
                                 [&] { ok = mbar_test(nb, np); });
            st++;
            if (ok && st <= LAST_ST) continue;
            if (st > NSTG - 2) break;
            mbar_wait(nb, np);
            if (st > LAST_ST) break;
        }
        conv_row<2, 4, true>(c, a1 + XSTG, a2 + XSTG, sA + 2 * CGRP, sB + 2 * CGRP, nop, [&] { bar_arrive(fw, 256); }, nop);
        fw = fw == BAR_FULL + NWG - 1 ? BAR_FULL : fw + 1;
        TLREC(3, 34);
        conv_row<3, 4, true>(c, a1 + XSTG + XROW, a2 + XSTG + XROW, sA + CBUF, sB + CBUF, [&] { bar_sync(BAR_EMPTY + 1, 256); }, nop, nop);
        conv_row<4, 4, false>(c, 0, 0, sA + CBUF + 2 * CGRP, sB + CBUF + 2 * CGRP, nop, nop, nop);
        bar_arrive(fw, 256);
        if (CFT == 1 && c.sink == 0x12345) sts32(S_RED + 36, c.sink);
        TLREC(3, 35);
    } else {
        asm volatile("setmaxnreg.inc.sync.aligned.u32 %0;" ::"n"(REG_CONS));
        const int wg = warp >> 2, wq = warp & 3;
        if (wg == 0) {
            const int kr = lane & 7;
#pragma unroll 1
            for (int i = 0; i < 3; i++) {
                const uint32_t base = S_W1 + (i * 4 + wq) * 6144;
                uint32_t r[12][4];
                mbar_wait(S_WBAR + 8 * i, 0);
                TLREC(3, 48 + i);
#pragma unroll
                for (int j = 0; j < 12; j++) lds128(r[j], base + kr * 768 + ((j >> 1) * 8 + ((kr + (j & 1) * 4 + (lane >> 3)) & 7)) * 16);
                __syncwarp();
#pragma unroll
                for (int j = 0; j < 12; j++)
                    sts128(base + kr * 16 + ((j >> 1) * 8 + ((kr + (j & 1) * 4 + (lane >> 3)) & 7)) * 128,
                           pack_h2(bf_lo(r[j][0]), bf_hi(r[j][0])), pack_h2(bf_lo(r[j][1]), bf_hi(r[j][1])),
                           pack_h2(bf_lo(r[j][2]), bf_hi(r[j][2])), pack_h2(bf_lo(r[j][3]), bf_hi(r[j][3])));
            }
        } else {
            constexpr int NW2 = 4 * (NWG - 1);
            uint32_t m = 0;
#pragma unroll 1
            for (int h = 0; h < 2; h++) {
                mbar_wait(S_WBAR + 24 + 8 * h, 0);
                if (wg == 1) TLREC(3, 51 + h);
#pragma unroll
                for (int j = 0; j < 72 / NW2; j++) {
                    uint32_t r[4];
                    lds128(r, S_W2 + h * (WBYTES / 2) + j * NW2 * 512 + (tid - 128) * 16);
                    m = habsmax(habsmax(m, r[0], r[1]), r[2], r[3]);
                }
            }
            m = __reduce_max_sync(0xffffffffu, max(m >> 16, m & 0xffffu));
            if (lane == 0) sts32(S_RED + (warp - 4) * 4, m);
            bar_sync(BAR_RED, 32 * NW2);
            m = __reduce_max_sync(0xffffffffu, lds32(S_RED + (lane & (NW2 - 1)) * 4));
            const int e = max(min(123 - (int)(m >> 7), 100), -15);
            const float wsc = __uint_as_float((uint32_t)(127 + e) << 23) * INV2A;
            if (tid == 128) sts32(S_RED + 32, ((uint32_t)(127 - e + (EPI == 1 ? 112 : 0)) << 7) * 0x10001u);
#pragma unroll 1
            for (int i = 0; i < 24 / NW2; i++) {
                const uint32_t base = S_W2 + (i * NW2 + warp - 4) * 3072;
                uint32_t r[6][4];
#pragma unroll
                for (int j = 0; j < 6; j++) lds128(r[j], base + (j / 3) * 1536 + (lane >> 2) * 192 + (j % 3) * 64 + (lane & 3) * 16);
                __syncwarp();
#pragma unroll
                for (int j = 0; j < 6; j++)
#pragma unroll
                    for (int k = 0; k < 4; k++)
                        sts32(base + (j / 3) * 1536 + ((j % 3) * 4 + k) * 128 + lane * 4, pack_h2(bf_lo(r[j][k]) * wsc, bf_hi(r[j][k]) * wsc));
            }
        }
        asm volatile("fence.proxy.async.shared::cta;" ::: "memory");
        TLREC(wg, 1);
        const uint32_t cbase = S_C + wq * CGRP + (lane & 15) * CPITCH + (lane >> 4) * 16;
        uint32_t goff = ((y0 + 2 * wg + (wq >> 1)) * IMG_W + w0 + (wq & 1) * 16 + (lane >> 2)) * (CH * 2) + (lane & 3) * 16;
        uint32_t H[96], a1[24], b[24], e[24], acc[24], res[24], st[2], t[16], sink = lane;
#pragma unroll
        for (int i = 0; i < 24; i++) { acc[i] = 0; res[i] = 0; }
        const uint32_t cb = cbase + wg * CBUF;
#define LDA(dst) _Pragma("unroll") for (int kk = 0; kk < 6; kk++) ldsm4(dst + 4 * kk, cb + kk * 32);
#define FETCH() { if (i < NT / 2 - 1) bar_sync(BAR_FULL + wg, 256); LDA(b) }
#define RELEASE() { if (i < NT / 2 - 2) bar_arrive(BAR_EMPTY + wg, 256);                                   \
                    if (wq == 0 && 2 * i + wg + 8 < NSTG && elect()) tma_x(&tmx, 2 * i + wg + 8, w0, y0); }
#define GL(p) gelu<8>(H + 8 * (p))
#define GA8(p) gelu_a<8>(t, H + 8 * (p))
#define GB8(p) gelu_b<8>(H + 8 * (p), t)
#define G1(j, k0, k1) gemm1<j, k0, k1>(H, a1, db)
#define G2(k0, k1) gemm2<k0, k1>(acc, H, db)
#define P(ks, j, kk) G2(ks, ks + 1); G1(j, kk, kk + 1)
#define Q(j, kk, ks) G1(j, kk, kk + 1); G2(ks, ks + 1)
#define F wg_fence()
#define C wg_commit()
#define W(n) wg_wait<n>()
#define RDY(j) pin<CN / 4>(H + (j) * (CN / 4))
#define CVT() epi_cvt(e, acc)
#define EO(r) epi_out<r>(e, res, osc2, out + gprev, i > 0)
#define RES(r) load_res<r>(res, x + gprev)
#define RESN(r) load_res<r>(res, x + goff)
#define GN(w0, n) gelu<n>(H + (w0))
#define GAN(w0, n) gelu_a<n>(t, H + (w0))
#define GBN(w0, n) gelu_b<n>(H + (w0), t)
#define LO(i0, i1) ln_out<i0, i1>(a1, b, st)
#define S SB1
        if (wg == 0) { bar_arrive(BAR_W1, 128 * NWG); bar_sync(BAR_W, 128); }
        else { bar_arrive(BAR_W2, 128 * NWG); bar_sync(BAR_W1, 128 * NWG); }
        TLREC(wg, 2);
        bar_sync(BAR_FULL + wg, 256);
        LDA(a1)
        bar_arrive(BAR_EMPTY + wg, 256);
        if (wq == 0 && elect()) {
            if (wg == 0) { tma_x(&tmx, 4, w0, y0); tma_x(&tmx, 5, w0, y0); }
            tma_x(&tmx, 6 + wg, w0, y0);
        }
        TLREC(wg, 3);
        ln_mean(a1, st); ln_var<0>(a1, st); ln_var<1>(a1, st); ln_out<0, 24>(a1, a1, st);
        TLREC(wg, 4);
        F; G1(0, 0, 6); C; W(0); RDY(0); GAN(0, T0);
        if (wg == 0) bar_sync(BAR_W2, 128 * NWG);
        const uint32_t osc2 = lds32(S_RED + 32);
        uint32_t gprev = goff;
#pragma unroll 1
        for (int i = 0; i < NT / 2; i++) {
            F; G1(1,0,6); C; S CVT(); GBN(0,12); EO(0); GN(12,12); S
            W(0); RDY(1); F; Q(2,0,0); Q(2,1,1); Q(2,2,2); Q(2,3,3); Q(2,4,4); G1(2,5,6); C; G2(5,6); C; EO(1); GN(24,12); S
            FETCH()
            F; G2(6,9); C; GN(36,12); S
            RELEASE()
            W(1); RDY(2); F; Q(3,0,9); Q(3,1,10); Q(3,2,11); G1(3,3,6); C; ln_mean(b, st); ln_var<0>(b, st); GN(48,12); S
            W(1); F; G2(12,15); C; ln_var<1>(b, st); GN(60,12); S
            W(1); RDY(3); F; G2(15,18); C; LO(0,24); GN(72,12); S
            W(1); F; Q(0,0,18); Q(0,1,19); Q(0,2,20); G1(0,3,6); C; RESN(0); RESN(1); S GN(84,12); S
            F; G2(21,24); C; W(1); RDY(0); GAN(0,12); S
            W(0); pin<24>(acc);
            gprev = goff;
            goff += TSTEP;
            TLREC(wg, 5 + i);
        }
        {
            const int i = 1;
            if (!(RESCARRY & 1)) RES(0);
            if (!(RESCARRY & 2)) RES(1);
            CVT(); EO(0); EO(1);
        }
        if (sink == 0x12345) sts32(S_RED + 36, sink);
        TLREC(wg, 77); TLRECG(wg, 79);
    }
}

typedef CUresult (*EncodeFn)(CUtensorMap*, CUtensorMapDataType, cuuint32_t, void*, const cuuint64_t*, const cuuint64_t*,
                             const cuuint32_t*, const cuuint32_t*, CUtensorMapInterleave, CUtensorMapSwizzle,
                             CUtensorMapL2promotion, CUtensorMapFloatOOBfill);

}

extern "C" void kernel_launch(void* const* d_in, const int* in_sizes, int n_in, void* d_out, int out_size) {
    static EncodeFn enc = nullptr;
    if (!enc) {
        void* fn = nullptr;
        cudaDriverEntryPointQueryResult qr;
        cudaGetDriverEntryPoint("cuTensorMapEncodeTiled", &fn, cudaEnableDefault, &qr);
        enc = (EncodeFn)fn;
        cudaFuncSetAttribute(replk_kernel, cudaFuncAttributeMaxDynamicSharedMemorySize, SMEM_BYTES);
    }
    CUtensorMap tm;
    const cuuint64_t gdim[3] = {CH, IMG_W, IMG_H};
    const cuuint64_t gstr[2] = {CH * 2, (cuuint64_t)IMG_W * CH * 2};
    const cuuint32_t box[3] = {CH, SW + 4, 2};
    const cuuint32_t estr[3] = {1, 1, 1};
    enc(&tm, CU_TENSOR_MAP_DATA_TYPE_BFLOAT16, 3, d_in[0], gdim, gstr, box, estr, CU_TENSOR_MAP_INTERLEAVE_NONE,
        CU_TENSOR_MAP_SWIZZLE_NONE, CU_TENSOR_MAP_L2_PROMOTION_L2_256B, CU_TENSOR_MAP_FLOAT_OOB_FILL_NONE);
    replk_kernel<<<(IMG_W / SW) * (IMG_H / RB), 384, SMEM_BYTES>>>(
        tm, (const uint8_t*)d_in[0], (const uint8_t*)d_in[1], (const uint8_t*)d_in[2], (const uint8_t*)d_in[3],
        (const uint8_t*)d_in[4], (uint8_t*)d_out, (uint64_t)(128 >> 4) << 32);
}
```

```cpp
#include <cuda_runtime.h>
#include <cuda_bf16.h>
#include <cuda_fp16.h>
#include <cuda.h>
#include <stdint.h>

namespace {

constexpr int IMG_H = 512, IMG_W = 512, CH = 96, HID = 384;
constexpr int SW = 32;
constexpr int RB = 64;
constexpr int NT = RB / 2;
constexpr int NSTG = NT + 2;
constexpr int NS = 4;
constexpr int NB = 2;
#define REG_CONS 184
#define REG_CONV 136
#define CN 96
#define T0 8
#define EPI 2
#define LNCVT 0

constexpr int XROW = (SW + 4) * CH * 2;
constexpr int XSTG = 2 * XROW;
constexpr int CPITCH = 208;
constexpr int CGRP = 16 * CPITCH + 64;
constexpr int CBUF = 4 * CGRP;
constexpr int WBYTES = CH * HID * 2;
constexpr uint32_t SB = 1024;
constexpr uint32_t S_W1 = SB;
constexpr uint32_t S_W2 = S_W1 + WBYTES;
constexpr uint32_t S_X = S_W2 + WBYTES;
constexpr uint32_t S_C = S_X + NS * XSTG;
constexpr uint32_t S_BAR = S_C + NB * CBUF;
constexpr uint32_t S_WBAR = S_BAR + 8 * NS;
constexpr uint32_t S_RED = S_WBAR + 8 * 6;
constexpr uint32_t S_ST = (S_RED + 64 + 127) / 128 * 128;
constexpr int SMEM_BYTES = S_ST + 256 - SB;
static_assert(SMEM_BYTES <= 232448, "smem");

constexpr int NWG = 2;
constexpr int BAR_FULL = 1, BAR_EMPTY = 4, BAR_W = 6, BAR_RED = 7, BAR_TURN = 8, BAR_CV = 11, BAR_W1 = 12, BAR_W2 = 13;

constexpr float GA = 0.3292034911525734f;
constexpr uint32_t GK2 = 0x40d940d9u;
constexpr float INV2A = 1.5188174288475842f;
constexpr uint32_t WSC2 = (uint32_t)(127 - 48) * 0x00800080u;
constexpr float LN_EPS = 1e-5f * 0x1p-96f;
constexpr float LN_OUT = GA * 0x1p-112f;

constexpr uint32_t D1 = (S_W1 >> 4) | ((48 * 128 >> 4) << 16);
constexpr uint32_t D3 = (S_ST >> 4) | ((128 >> 4) << 16);
constexpr uint32_t D2 = (S_W2 >> 4) | ((12 * 128 >> 4) << 16);

template <int SCALE_D> __device__ __forceinline__ void wg_n64_h(uint32_t* d, const uint32_t* a, uint64_t desc);
template <>
__device__ __forceinline__ void wg_n64_h<0>(uint32_t* d, const uint32_t* a, uint64_t desc) {
    asm volatile("wgmma.mma_async.sync.aligned.m64n64k16.f16.f16.f16 {"
        "%0,%1,%2,%3,%4,%5,%6,%7,%8,%9,%10,%11,%12,%13,%14,%15},"
        "{%16,%17,%18,%19}, %20, 0, 1, 1, 1;"
        : "=r"(d[0]), "=r"(d[1]), "=r"(d[2]), "=r"(d[3]), "=r"(d[4]), "=r"(d[5]), "=r"(d[6]), "=r"(d[7]),
          "=r"(d[8]), "=r"(d[9]), "=r"(d[10]), "=r"(d[11]), "=r"(d[12]), "=r"(d[13]), "=r"(d[14]), "=r"(d[15])
        : "r"(a[0]), "r"(a[1]), "r"(a[2]), "r"(a[3]), "l"(desc));
}
template <>
__device__ __forceinline__ void wg_n64_h<1>(uint32_t* d, const uint32_t* a, uint64_t desc) {
    asm volatile("wgmma.mma_async.sync.aligned.m64n64k16.f16.f16.f16 {"
        "%0,%1,%2,%3,%4,%5,%6,%7,%8,%9,%10,%11,%12,%13,%14,%15},"
        "{%16,%17,%18,%19}, %20, 1, 1, 1, 1;"
        : "+r"(d[0]), "+r"(d[1]), "+r"(d[2]), "+r"(d[3]), "+r"(d[4]), "+r"(d[5]), "+r"(d[6]), "+r"(d[7]),
          "+r"(d[8]), "+r"(d[9]), "+r"(d[10]), "+r"(d[11]), "+r"(d[12]), "+r"(d[13]), "+r"(d[14]), "+r"(d[15])
        : "r"(a[0]), "r"(a[1]), "r"(a[2]), "r"(a[3]), "l"(desc));
}
template <int SCALE_D> __device__ __forceinline__ void wg_n96_h(uint32_t* d, const uint32_t* a, uint64_t desc);
template <>
__device__ __forceinline__ void wg_n96_h<0>(uint32_t* d, const uint32_t* a, uint64_t desc) {
    asm volatile("wgmma.mma_async.sync.aligned.m64n96k16.f16.f16.f16 {"
        "%0,%1,%2,%3,%4,%5,%6,%7,%8,%9,%10,%11,%12,%13,%14,%15,"
        "%16,%17,%18,%19,%20,%21,%22,%23},"
        "{%24,%25,%26,%27}, %28, 0, 1, 1, 1;"
        : "=r"(d[0]), "=r"(d[1]), "=r"(d[2]), "=r"(d[3]), "=r"(d[4]), "=r"(d[5]), "=r"(d[6]), "=r"(d[7]),
          "=r"(d[8]), "=r"(d[9]), "=r"(d[10]), "=r"(d[11]), "=r"(d[12]), "=r"(d[13]), "=r"(d[14]), "=r"(d[15]),
          "=r"(d[16]), "=r"(d[17]), "=r"(d[18]), "=r"(d[19]), "=r"(d[20]), "=r"(d[21]), "=r"(d[22]), "=r"(d[23])
        : "r"(a[0]), "r"(a[1]), "r"(a[2]), "r"(a[3]), "l"(desc));
}
template <>
__device__ __forceinline__ void wg_n96_h<1>(uint32_t* d, const uint32_t* a, uint64_t desc) {
    asm volatile("wgmma.mma_async.sync.aligned.m64n96k16.f16.f16.f16 {"
        "%0,%1,%2,%3,%4,%5,%6,%7,%8,%9,%10,%11,%12,%13,%14,%15,"
        "%16,%17,%18,%19,%20,%21,%22,%23},"
        "{%24,%25,%26,%27}, %28, 1, 1, 1, 1;"
        : "+r"(d[0]), "+r"(d[1]), "+r"(d[2]), "+r"(d[3]), "+r"(d[4]), "+r"(d[5]), "+r"(d[6]), "+r"(d[7]),
          "+r"(d[8]), "+r"(d[9]), "+r"(d[10]), "+r"(d[11]), "+r"(d[12]), "+r"(d[13]), "+r"(d[14]), "+r"(d[15]),
          "+r"(d[16]), "+r"(d[17]), "+r"(d[18]), "+r"(d[19]), "+r"(d[20]), "+r"(d[21]), "+r"(d[22]), "+r"(d[23])
        : "r"(a[0]), "r"(a[1]), "r"(a[2]), "r"(a[3]), "l"(desc));
}
template <int SCALE_D> __device__ __forceinline__ void wg_n128_h(uint32_t* d, const uint32_t* a, uint64_t desc);
template <>
__device__ __forceinline__ void wg_n128_h<0>(uint32_t* d, const uint32_t* a, uint64_t desc) {
    asm volatile("wgmma.mma_async.sync.aligned.m64n128k16.f16.f16.f16 {"
        "%0,%1,%2,%3,%4,%5,%6,%7,%8,%9,%10,%11,%12,%13,%14,%15,"
        "%16,%17,%18,%19,%20,%21,%22,%23,%24,%25,%26,%27,%28,%29,%30,%31},"
        "{%32,%33,%34,%35}, %36, 0, 1, 1, 1;"
        : "=r"(d[0]), "=r"(d[1]), "=r"(d[2]), "=r"(d[3]), "=r"(d[4]), "=r"(d[5]), "=r"(d[6]), "=r"(d[7]),
          "=r"(d[8]), "=r"(d[9]), "=r"(d[10]), "=r"(d[11]), "=r"(d[12]), "=r"(d[13]), "=r"(d[14]), "=r"(d[15]),
          "=r"(d[16]), "=r"(d[17]), "=r"(d[18]), "=r"(d[19]), "=r"(d[20]), "=r"(d[21]), "=r"(d[22]), "=r"(d[23]),
          "=r"(d[24]), "=r"(d[25]), "=r"(d[26]), "=r"(d[27]), "=r"(d[28]), "=r"(d[29]), "=r"(d[30]), "=r"(d[31])
        : "r"(a[0]), "r"(a[1]), "r"(a[2]), "r"(a[3]), "l"(desc));
}
template <>
__device__ __forceinline__ void wg_n128_h<1>(uint32_t* d, const uint32_t* a, uint64_t desc) {
    asm volatile("wgmma.mma_async.sync.aligned.m64n128k16.f16.f16.f16 {"
        "%0,%1,%2,%3,%4,%5,%6,%7,%8,%9,%10,%11,%12,%13,%14,%15,"
        "%16,%17,%18,%19,%20,%21,%22,%23,%24,%25,%26,%27,%28,%29,%30,%31},"
        "{%32,%33,%34,%35}, %36, 1, 1, 1, 1;"
        : "+r"(d[0]), "+r"(d[1]), "+r"(d[2]), "+r"(d[3]), "+r"(d[4]), "+r"(d[5]), "+r"(d[6]), "+r"(d[7]),
          "+r"(d[8]), "+r"(d[9]), "+r"(d[10]), "+r"(d[11]), "+r"(d[12]), "+r"(d[13]), "+r"(d[14]), "+r"(d[15]),
          "+r"(d[16]), "+r"(d[17]), "+r"(d[18]), "+r"(d[19]), "+r"(d[20]), "+r"(d[21]), "+r"(d[22]), "+r"(d[23]),
          "+r"(d[24]), "+r"(d[25]), "+r"(d[26]), "+r"(d[27]), "+r"(d[28]), "+r"(d[29]), "+r"(d[30]), "+r"(d[31])
        : "r"(a[0]), "r"(a[1]), "r"(a[2]), "r"(a[3]), "l"(desc));
}
template <int SCALE_D> __device__ __forceinline__ void wg_n192_h(uint32_t* d, const uint32_t* a, uint64_t desc);
template <>
__device__ __forceinline__ void wg_n192_h<0>(uint32_t* d, const uint32_t* a, uint64_t desc) {
    asm volatile("wgmma.mma_async.sync.aligned.m64n192k16.f16.f16.f16 {"
        "%0,%1,%2,%3,%4,%5,%6,%7,%8,%9,%10,%11,%12,%13,%14,%15,"
        "%16,%17,%18,%19,%20,%21,%22,%23,%24,%25,%26,%27,%28,%29,%30,%31,"
        "%32,%33,%34,%35,%36,%37,%38,%39,%40,%41,%42,%43,%44,%45,%46,%47},"
        "{%48,%49,%50,%51}, %52, 0, 1, 1, 1;"
        : "=r"(d[0]), "=r"(d[1]), "=r"(d[2]), "=r"(d[3]), "=r"(d[4]), "=r"(d[5]), "=r"(d[6]), "=r"(d[7]),
          "=r"(d[8]), "=r"(d[9]), "=r"(d[10]), "=r"(d[11]), "=r"(d[12]), "=r"(d[13]), "=r"(d[14]), "=r"(d[15]),
          "=r"(d[16]), "=r"(d[17]), "=r"(d[18]), "=r"(d[19]), "=r"(d[20]), "=r"(d[21]), "=r"(d[22]), "=r"(d[23]),
          "=r"(d[24]), "=r"(d[25]), "=r"(d[26]), "=r"(d[27]), "=r"(d[28]), "=r"(d[29]), "=r"(d[30]), "=r"(d[31]),
          "=r"(d[32]), "=r"(d[33]), "=r"(d[34]), "=r"(d[35]), "=r"(d[36]), "=r"(d[37]), "=r"(d[38]), "=r"(d[39]),
          "=r"(d[40]), "=r"(d[41]), "=r"(d[42]), "=r"(d[43]), "=r"(d[44]), "=r"(d[45]), "=r"(d[46]), "=r"(d[47])
        : "r"(a[0]), "r"(a[1]), "r"(a[2]), "r"(a[3]), "l"(desc));
}
template <>
__device__ __forceinline__ void wg_n192_h<1>(uint32_t* d, const uint32_t* a, uint64_t desc) {
    asm volatile("wgmma.mma_async.sync.aligned.m64n192k16.f16.f16.f16 {"
        "%0,%1,%2,%3,%4,%5,%6,%7,%8,%9,%10,%11,%12,%13,%14,%15,"
        "%16,%17,%18,%19,%20,%21,%22,%23,%24,%25,%26,%27,%28,%29,%30,%31,"
        "%32,%33,%34,%35,%36,%37,%38,%39,%40,%41,%42,%43,%44,%45,%46,%47},"
        "{%48,%49,%50,%51}, %52, 1, 1, 1, 1;"
        : "+r"(d[0]), "+r"(d[1]), "+r"(d[2]), "+r"(d[3]), "+r"(d[4]), "+r"(d[5]), "+r"(d[6]), "+r"(d[7]),
          "+r"(d[8]), "+r"(d[9]), "+r"(d[10]), "+r"(d[11]), "+r"(d[12]), "+r"(d[13]), "+r"(d[14]), "+r"(d[15]),
          "+r"(d[16]), "+r"(d[17]), "+r"(d[18]), "+r"(d[19]), "+r"(d[20]), "+r"(d[21]), "+r"(d[22]), "+r"(d[23]),
          "+r"(d[24]), "+r"(d[25]), "+r"(d[26]), "+r"(d[27]), "+r"(d[28]), "+r"(d[29]), "+r"(d[30]), "+r"(d[31]),
          "+r"(d[32]), "+r"(d[33]), "+r"(d[34]), "+r"(d[35]), "+r"(d[36]), "+r"(d[37]), "+r"(d[38]), "+r"(d[39]),
          "+r"(d[40]), "+r"(d[41]), "+r"(d[42]), "+r"(d[43]), "+r"(d[44]), "+r"(d[45]), "+r"(d[46]), "+r"(d[47])
        : "r"(a[0]), "r"(a[1]), "r"(a[2]), "r"(a[3]), "l"(desc));
}

#define HINT 0
constexpr uint64_t POL_EF = 0x12F0000000000000ull;
__device__ __forceinline__ void wg_fence() { asm volatile("wgmma.fence.sync.aligned;" ::: "memory"); }
__device__ __forceinline__ void wg_commit() { asm volatile("wgmma.commit_group.sync.aligned;" ::: "memory"); }
template <int N> __device__ __forceinline__ void wg_wait() { asm volatile("wgmma.wait_group.sync.aligned %0;" ::"n"(N) : "memory"); }
template <int N> __device__ __forceinline__ void pin(uint32_t* r) {
#pragma unroll
    for (int i = 0; i < N; i++) asm volatile("" : "+r"(r[i])::"memory");
}
__device__ __forceinline__ void sbar() { asm volatile("griddepcontrol.launch_dependents;" ::: "memory"); }

#define CK64 0
__device__ __forceinline__ void cfence(uint32_t& sink) {
    uint32_t ck;
    asm volatile("mov.u32 %0, %%clock;" : "=r"(ck)::"memory");
    sink ^= ck;
}
#define SFT 0
__device__ __forceinline__ void bar_sync(int id, int n) { asm volatile("bar.sync %0, %1;" ::"r"(id), "r"(n) : "memory"); }
__device__ __forceinline__ void bar_arrive(int id, int n) { asm volatile("bar.arrive %0, %1;" ::"r"(id), "r"(n) : "memory"); }
__device__ __forceinline__ void mbar_init(uint32_t a, uint32_t cnt) { asm volatile("mbarrier.init.shared::cta.b64 [%0], %1;" ::"r"(a), "r"(cnt) : "memory"); }
__device__ __forceinline__ void mbar_expect_tx(uint32_t a, uint32_t bytes) { asm volatile("mbarrier.arrive.expect_tx.shared::cta.b64 _, [%0], %1;" ::"r"(a), "r"(bytes) : "memory"); }
__device__ __forceinline__ bool mbar_try(uint32_t a, uint32_t parity) {
    uint32_t ok;
    asm volatile("{.reg .pred p; mbarrier.try_wait.parity.shared::cta.b64 p, [%1], %2; selp.u32 %0, 1, 0, p;}" : "=r"(ok) : "r"(a), "r"(parity) : "memory");
    return ok;
}
__device__ __forceinline__ void mbar_wait(uint32_t a, uint32_t parity) {
    asm volatile("{.reg .pred p, q; .reg .u32 g; mov.u32 g, 0;\n"
                 "L: mbarrier.try_wait.parity.shared::cta.b64 p, [%0], %1;\n"
                 "add.u32 g, g, 1; setp.lt.and.u32 q, g, 0x400000, !p; @q bra L;}" ::"r"(a), "r"(parity) : "memory");
}
__device__ __forceinline__ bool mbar_test(uint32_t a, uint32_t parity) {
    uint32_t ok;
    asm volatile("{.reg .pred p; mbarrier.test_wait.parity.shared::cta.b64 p, [%1], %2; selp.u32 %0, 1, 0, p;}" : "=r"(ok) : "r"(a), "r"(parity) : "memory");
    return ok;
}
__device__ __forceinline__ bool elect() {
    uint32_t ok;
    asm volatile("{.reg .pred p; elect.sync _|p, 0xffffffff; selp.u32 %0, 1, 0, p;}" : "=r"(ok));
    return ok;
}
__device__ __forceinline__ void tma_x(const CUtensorMap* tm, int slot, int q, int xq, int yq) {
    const uint32_t bar = S_BAR + 8 * slot;
    mbar_expect_tx(bar, XSTG / 4);
    asm volatile("cp.async.bulk.tensor.3d.shared::cluster.global.mbarrier::complete_tx::bytes [%0], [%1, {%3, %4, %5}], [%2];"
                 ::"r"(S_X + slot * XSTG + q * (XSTG / 4)), "l"(tm), "r"(bar), "r"(0), "r"(xq), "r"(yq) : "memory");
}
__device__ __forceinline__ void bulk_load(uint32_t dst, const void* src, uint32_t bytes, uint32_t bar) {
    asm volatile("cp.async.bulk.shared::cluster.global.mbarrier::complete_tx::bytes [%0], [%1], %2, [%3];"
                 ::"r"(dst), "l"(src), "r"(bytes), "r"(bar) : "memory");
}
__device__ __forceinline__ uint32_t lds32(uint32_t a) { uint32_t v; asm volatile("ld.shared.b32 %0, [%1];" : "=r"(v) : "r"(a)); return v; }
__device__ __forceinline__ void lds128(uint32_t* r, uint32_t a) { asm volatile("ld.shared.v4.b32 {%0,%1,%2,%3}, [%4];" : "=r"(r[0]), "=r"(r[1]), "=r"(r[2]), "=r"(r[3]) : "r"(a)); }
__device__ __forceinline__ void sts32(uint32_t a, uint32_t v) { asm volatile("st.shared.b32 [%0], %1;" ::"r"(a), "r"(v)); }
__device__ __forceinline__ void sts128(uint32_t a, uint32_t x, uint32_t y, uint32_t z, uint32_t w) { asm volatile("st.shared.v4.b32 [%0], {%1,%2,%3,%4};" ::"r"(a), "r"(x), "r"(y), "r"(z), "r"(w)); }
__device__ __forceinline__ void ldsm4(uint32_t* r, uint32_t a) {
    asm volatile("ldmatrix.sync.aligned.m8n8.x4.shared.b16 {%0,%1,%2,%3}, [%4];" : "=r"(r[0]), "=r"(r[1]), "=r"(r[2]), "=r"(r[3]) : "r"(a));
}
__device__ __forceinline__ void ldsm4s(uint32_t& r0, uint32_t& r1, uint32_t& r2, uint32_t& r3, uint32_t a) {
    asm volatile("ldmatrix.sync.aligned.m8n8.x4.shared.b16 {%0,%1,%2,%3}, [%4];" : "=r"(r0), "=r"(r1), "=r"(r2), "=r"(r3) : "r"(a));
}
__device__ __forceinline__ void ldsm2s(uint32_t& r0, uint32_t& r1, uint32_t a) {
    asm volatile("ldmatrix.sync.aligned.m8n8.x2.shared.b16 {%0,%1}, [%2];" : "=r"(r0), "=r"(r1) : "r"(a));
}
__device__ __forceinline__ void stsm4(uint32_t a, const uint32_t* r) {
    asm volatile("stmatrix.sync.aligned.m8n8.x4.shared.b16 [%4], {%0,%1,%2,%3};" ::"r"(r[0]), "r"(r[1]), "r"(r[2]), "r"(r[3]), "r"(a));
}
__device__ __forceinline__ void ldg128(uint32_t* r, const void* p) {
    asm volatile("ld.global.nc.L1::no_allocate.v4.b32 {%0,%1,%2,%3}, [%4];" : "=r"(r[0]), "=r"(r[1]), "=r"(r[2]), "=r"(r[3]) : "l"(p));
}
__device__ __forceinline__ void stg128(void* p, uint32_t x, uint32_t y, uint32_t z, uint32_t w) {
    asm volatile("st.global.L1::no_allocate.v4.b32 [%0], {%1,%2,%3,%4};" ::"l"(p), "r"(x), "r"(y), "r"(z), "r"(w));
}
__device__ __forceinline__ uint32_t bfma(uint32_t a, uint32_t b, uint32_t c) { uint32_t d; asm("fma.rn.bf16x2 %0, %1, %2, %3;" : "=r"(d) : "r"(a), "r"(b), "r"(c)); return d; }
__device__ __forceinline__ uint32_t bmul(uint32_t a, uint32_t b) { uint32_t d; asm("mul.rn.bf16x2 %0, %1, %2;" : "=r"(d) : "r"(a), "r"(b)); return d; }
__device__ __forceinline__ uint32_t vfma(uint32_t a, uint32_t b, uint32_t c) { uint32_t d; asm volatile("fma.rn.bf16x2 %0, %1, %2, %3;" : "=r"(d) : "r"(a), "r"(b), "r"(c)); return d; }
__device__ __forceinline__ void vacc(uint32_t& d, uint32_t a, uint32_t b) { asm volatile("fma.rn.bf16x2 %0, %1, %2, %0;" : "+r"(d) : "r"(a), "r"(b)); }
__device__ __forceinline__ uint32_t vmul(uint32_t a, uint32_t b) { uint32_t d; asm volatile("mul.rn.bf16x2 %0, %1, %2;" : "=r"(d) : "r"(a), "r"(b)); return d; }
__device__ __forceinline__ uint32_t badd(uint32_t a, uint32_t b) { uint32_t d; asm("add.rn.bf16x2 %0, %1, %2;" : "=r"(d) : "r"(a), "r"(b)); return d; }
__device__ __forceinline__ uint32_t habsmax(uint32_t m, uint32_t a, uint32_t b) { return __vimax3_u16x2(m, a & 0x7fff7fffu, b & 0x7fff7fffu); }
__device__ __forceinline__ float bf_lo(uint32_t v) { uint32_t d; asm("prmt.b32 %0, %1, 0, 0x1044;" : "=r"(d) : "r"(v)); return __uint_as_float(d); }
__device__ __forceinline__ float bf_hi(uint32_t v) { return __uint_as_float(v & 0xffff0000u); }
__device__ __forceinline__ uint32_t pack_h2(float lo, float hi) { uint32_t d; asm("cvt.rn.f16x2.f32 %0, %1, %2;" : "=r"(d) : "f"(hi), "f"(lo)); return d; }
__device__ __forceinline__ uint32_t pack_b2(float lo, float hi) { uint32_t d; asm("cvt.rn.bf16x2.f32 %0, %1, %2;" : "=r"(d) : "f"(hi), "f"(lo)); return d; }

template <int N> __device__ __forceinline__ void gelu(uint32_t* h) {
#pragma unroll
    for (int i = 0; i < N; i++) {
        uint32_t p, u, t;
        asm("fma.rn.f16x2 %0, %1, %1, %2;" : "=r"(p) : "r"(h[i]), "r"(GK2));
        asm("mul.rn.f16x2 %0, %1, %2;" : "=r"(u) : "r"(h[i]), "r"(p));
        asm("tanh.approx.f16x2 %0, %1;" : "=r"(t) : "r"(u));
        asm("fma.rn.f16x2 %0, %1, %2, %1;" : "=r"(h[i]) : "r"(h[i]), "r"(t));
    }
    pin<N>(h);
}
template <int N> __device__ __forceinline__ void gelu_a(uint32_t* t, const uint32_t* h) {
#pragma unroll
    for (int i = 0; i < N; i++) {
        uint32_t p, u;
        asm("fma.rn.f16x2 %0, %1, %1, %2;" : "=r"(p) : "r"(h[i]), "r"(GK2));
        asm("mul.rn.f16x2 %0, %1, %2;" : "=r"(u) : "r"(h[i]), "r"(p));
        asm("tanh.approx.f16x2 %0, %1;" : "=r"(t[i]) : "r"(u));
    }
    pin<N>(t);
}
template <int N> __device__ __forceinline__ void gelu_b(uint32_t* h, const uint32_t* t) {
#pragma unroll
    for (int i = 0; i < N; i++) asm volatile("fma.rn.f16x2 %0, %1, %2, %1;" : "=r"(h[i]) : "r"(h[i]), "r"(t[i]));
}
#define RESCARRY 1
#define MIDW 12
#define OV 1
#define SB2 SB1
#define SB3 SB1
#define SB1 cfence(sink);

#define PEEL0 1
#define PEEL1 1
#define EDGE1 1
#define PRO 6
#define PEELT 1
#define CSINK lane
#define CFT 1
#define CORDER 1
template <int S, int P, int ILO, int IHI>
__device__ __forceinline__ void conv_col(uint32_t x, const uint32_t* w, uint32_t (&acc)[4][S], uint32_t (&o)[S]) {
#pragma unroll
    for (int j = 4; j >= 0; j--) {
        const int q = P - j;
        if (q < 0 || q >= S) continue;
#pragma unroll
        for (int i = IHI; i >= ILO; i--) {
            uint32_t& d = (i == 4) ? o[q] : acc[i == 4 ? 0 : 3 - i][q];
            const uint32_t ww = w[2 * (i * 5 + j)];
            if (j > 0) vacc(d, x, ww);
            else if (i == 4 && CORDER == 1) { d = acc[0][q]; vacc(d, x, ww); }
            else d = (i == 0) ? vmul(x, ww) : vfma(x, ww, acc[i == 0 ? 0 : 4 - i][q]);
        }
    }
}
#define CFENCE 0x10
struct Conv {
    uint32_t w[50];
    uint32_t accA[4][8], accB[4][4];
    uint32_t sink;
    uint32_t xa[12], xb[8];
};
template <int K> __device__ __forceinline__ void conv_ld(Conv& c, uint32_t a1) { ldsm4s(c.xa[2 * K + 2], c.xb[2 * K], c.xa[2 * K + 3], c.xb[2 * K + 1], a1 + K * 2 * CH * 2); }
#define CFN(n) { if ((CFENCE >> n) & 1) cfence(c.sink); }
template <typename Fn>
__device__ __forceinline__ void conv_out(Conv& c, uint32_t sA, uint32_t sB, Fn before_store) {
    uint32_t oA[8], oB[4];
#define CA(p) conv_col<8, p, 4, 4>(c.xa[p], c.w + 1, c.accA, oA)
#define CB(p) conv_col<4, p, 4, 4>(c.xb[p], c.w, c.accB, oB)
    CA(0); CA(1); CA(2); CB(0); CA(3); CB(1); CA(4); CB(2); CA(5); CB(3); CA(6); CB(4); CA(7); CB(5);
    before_store();
    stsm4(sA, oA);
    CA(8); CB(6); CA(9); CB(7); CA(10); CA(11);
    stsm4(sB, oB);
    stsm4(sA + 4 * CPITCH, oA + 4);
#undef CA
#undef CB
}
template <int ILO, int IHI, typename Fn>
__device__ __forceinline__ void conv_rest(Conv& c, uint32_t a1, uint32_t a2, Fn mid) {
    uint32_t oA[8], oB[4];
#define CA(p) conv_col<8, p, ILO, IHI>(c.xa[p], c.w + 1, c.accA, oA)
#define CB(p) conv_col<4, p, ILO, IHI>(c.xb[p], c.w, c.accB, oB)
    CA(0); CA(1); CFN(0)
    ldsm2s(c.xa[0], c.xa[1], a2);
    CA(2); CB(0); CA(3); CB(1); CFN(1)
    conv_ld<0>(c, a1);
    CA(4); CB(2); CA(5); CB(3); CFN(2)
    conv_ld<1>(c, a1);
    CA(6); CB(4); CA(7); CB(5); CFN(3)
    conv_ld<2>(c, a1);
    mid();
    CA(8); CB(6); CA(9); CB(7); CFN(4)
    conv_ld<3>(c, a1);
    CA(10); CA(11); CFN(5)
    ldsm2s(c.xa[10], c.xa[11], a2 + 10 * CH * 2);
#undef CA
#undef CB
}

__device__ __forceinline__ uint64_t mkd(uint64_t db, uint32_t lo) { uint64_t d; asm volatile("add.u64 %0, %1, %2;" : "=l"(d) : "l"(db), "l"((uint64_t)lo)); return d; }
template <int J, int K0, int K1> __device__ __forceinline__ void gemm1(uint32_t* H, const uint32_t* a1, uint64_t db) {
#pragma unroll
    for (int kk = K0; kk < K1; kk++) {
        const uint64_t d = mkd(db, D1 + ((2 * kk * 48 + J * (CN / 8)) * 128 >> 4));
        if (kk == 0) wg_n96_h<0>(H + J * 24, a1, d);
        else wg_n96_h<1>(H + J * 24, a1 + 4 * kk, d);
    }
}
template <int K0, int K1> __device__ __forceinline__ void gemm2(uint32_t* acc, const uint32_t* H, uint64_t db) {
#pragma unroll
    for (int ks = K0; ks < K1; ks++) {
        const uint64_t d = mkd(db, D2 + (2 * ks * 12 * 128 >> 4));
        if (ks == 0) wg_n96_h<0>(acc, H, d);
        else wg_n96_h<1>(acc, H + 4 * ks, d);
    }
}

__device__ __forceinline__ float quad_sum(uint32_t v) {
    float s = bf_lo(v) + bf_hi(v);
    s += __shfl_xor_sync(0xffffffffu, s, 1);
    s += __shfl_xor_sync(0xffffffffu, s, 2);
    return s;
}
template <int r> __device__ __forceinline__ void ln_part(const uint32_t* a, uint32_t* sq) {
    uint32_t s[6], q[2];
#pragma unroll
    for (int i = 0; i < 6; i++) s[i] = badd(a[4 * i + r], a[4 * i + 2 + r]);
    sq[r] = badd(badd(badd(s[0], s[1]), badd(s[2], s[3])), badd(s[4], s[5]));
#pragma unroll
    for (int i = 0; i < 12; i++) q[i & 1] = (i < 2) ? bmul(a[2 * i + r], a[2 * i + r]) : bfma(a[2 * i + r], a[2 * i + r], q[i & 1]);
    sq[2 + r] = badd(q[0], q[1]);
    pin<1>(sq + r); pin<1>(sq + 2 + r);
}
__device__ __forceinline__ void ln_mma(float* d, const uint32_t* sq, uint64_t db) {
    asm volatile("wgmma.mma_async.sync.aligned.m64n8k16.f32.bf16.bf16 {%0,%1,%2,%3}, {%4,%5,%6,%7}, %8, 0, 1, 1, 1;"
                 : "=f"(d[0]), "=f"(d[1]), "=f"(d[2]), "=f"(d[3]) : "r"(sq[0]), "r"(sq[1]), "r"(sq[2]), "r"(sq[3]), "l"(mkd(db, D3)));
}
__device__ __forceinline__ uint32_t ln_pack(float v, float m) {
    float rs;
    asm("rsqrt.approx.ftz.f32 %0, %1;" : "=f"(rs) : "f"(v));
    rs *= LN_OUT;
    return pack_b2(rs, m * rs);
}
__device__ __forceinline__ bool ln_fin(float* d, uint32_t* st) {
    asm volatile("" : "+f"(d[0]), "+f"(d[1]), "+f"(d[2]), "+f"(d[3])::"memory");
    bool risky = false;
#pragma unroll
    for (int r = 0; r < 2; r++) {
        const float m = d[2 * r] * (-1.f / CH);
        const float t = fmaf(d[2 * r + 1], 1.f / CH, LN_EPS);
        const float v = fmaf(-m, m, t);
        risky |= !(v + v >= t);
        st[r] = ln_pack(v, m);
        d[2 * r] = m;
    }
    pin<2>(st);
    return __any_sync(0xffffffffu, risky);
}
__device__ __forceinline__ void ln_fix(uint32_t* a, const float* d, uint32_t* st) {
#pragma unroll
    for (int r = 0; r < 2; r++) {
        const uint32_t m2 = pack_b2(d[2 * r], d[2 * r]);
        uint32_t q[2];
#pragma unroll
        for (int i = 0; i < 12; i++) {
            a[2 * i + r] = badd(a[2 * i + r], m2);
            q[i & 1] = (i < 2) ? bmul(a[2 * i + r], a[2 * i + r]) : bfma(a[2 * i + r], a[2 * i + r], q[i & 1]);
        }
        st[r] = ln_pack(fmaf(quad_sum(badd(q[0], q[1])), 1.f / CH, LN_EPS), 0.f);
    }
}
template <int I0, int I1> __device__ __forceinline__ void ln_out(uint32_t* a, const uint32_t* b, const uint32_t* st) {
#pragma unroll
    for (int i = I0; i < I1; i++) {
        uint32_t v;
        asm("{.reg .b16 l, h; .reg .b32 ll, hh; mov.b32 {l, h}, %2; mov.b32 ll, {l, l}; mov.b32 hh, {h, h}; fma.rn.bf16x2 %0, %1, ll, hh;}"
            : "=r"(v) : "r"(b[i]), "r"(st[i & 1]));
        a[i] = v + 7u * (v & 0x7fff7fffu);
        pin<1>(a + i);
    }
}

__device__ __forceinline__ void epi_cvt(uint32_t* e, const uint32_t* acc) {
#pragma unroll
    for (int i = 0; i < 24; i++) {
        const uint32_t hv = acc[i];
        const float2 f = __half22float2(*reinterpret_cast<const __half2*>(&hv));
        e[i] = pack_b2(f.x, f.y);
    }
    pin<24>(e);
}
template <int R> __device__ __forceinline__ void epi_out(const uint32_t* e, const uint32_t* res, uint32_t osc2, uint8_t* gp, bool on) {
#pragma unroll
    for (int i = 0; i < 3; i++) {
        uint32_t o[4];
#pragma unroll
        for (int jj = 0; jj < 4; jj++) o[jj] = vfma(e[2 * (4 * i + jj) + R], osc2, res[(R * 3 + i) * 4 + jj]);
        asm volatile("{.reg .pred p; setp.ne.u32 p, %5, 0; @p st.global.L1::no_allocate.v4.b32 [%0], {%1,%2,%3,%4};}"
                     ::"l"(gp + R * 8 * CH * 2 + i * 64), "r"(o[0]), "r"(o[1]), "r"(o[2]), "r"(o[3]), "r"((uint32_t)(on && (!(HINT & 8) || osc2 == 0))));
    }
}
template <int R> __device__ __forceinline__ void load_res(uint32_t* res, const uint8_t* xg) {
#pragma unroll
    for (int i = 0; i < 3; i++) ldg128(res + (R * 3 + i) * 4, xg + R * 8 * CH * 2 + i * 64);
}

#define TLREC(role, idx)
#define TLRECG(role, idx)

constexpr int TSTEP = 2 * NWG * IMG_W * CH * 2;

__global__ void __launch_bounds__(384, 1)
replk_kernel(const __grid_constant__ CUtensorMap tmx, const uint8_t* __restrict__ x, const uint8_t* __restrict__ dwl,
             const uint8_t* __restrict__ dws, const uint8_t* __restrict__ w1, const uint8_t* __restrict__ w2,
             uint8_t* __restrict__ out, const uint64_t db) {
    extern __shared__ __align__(1024) uint8_t smem[];
#define ROT 2
    const int tid = (threadIdx.x + ROT * 128) % 384, lane = tid & 31;
    const int warp = __shfl_sync(0xffffffffu, tid >> 5, 0);
    const int w0 = (blockIdx.x % (IMG_W / SW)) * SW, y0 = (blockIdx.x / (IMG_W / SW)) * RB;
    if (warp < 8) { TLREC(warp >> 2, 0); TLRECG(warp >> 2, 78); }

    if (warp >= 8) {
        asm volatile("setmaxnreg.dec.sync.aligned.u32 %0;" ::"n"(REG_CONV));
        const int cw = warp - 8;
        if (cw == 0 && elect()) {
            if ((uint32_t)__cvta_generic_to_shared(smem) != SB) __trap();
#pragma unroll
            for (int s = 0; s < NS + 6; s++) mbar_init(S_BAR + 8 * s, s < NS ? 4 : 1);
            asm volatile("fence.mbarrier_init.release.cluster;" ::: "memory");
            TLREC(3, 43);
            mbar_expect_tx(S_WBAR + 40, 34 * CH * 2);
            bulk_load(S_C, dws, 25 * CH * 2, S_WBAR + 40);
            bulk_load(S_C + 25 * CH * 2, dwl, 9 * CH * 2, S_WBAR + 40);
            TLREC(3, 44);
#define LX(s) { _Pragma("unroll") for (int q = 0; q < 4; q++) tma_x(&tmx, s, q, w0 - 2 + (q & 1) * 18, y0 - 2 + 2 * s + (q >> 1)); }
#define LW1(i) { mbar_expect_tx(S_WBAR + 8 * i, WBYTES / 3); bulk_load(S_W1 + i * (WBYTES / 3), w1 + i * (WBYTES / 3), WBYTES / 3, S_WBAR + 8 * i); }
#define LW2(i) { mbar_expect_tx(S_WBAR + 24 + 8 * i, WBYTES / 2); bulk_load(S_W2 + i * (WBYTES / 2), w2 + i * (WBYTES / 2), WBYTES / 2, S_WBAR + 24 + 8 * i); }
            LX(0) LW1(0) LX(1) LW1(1) LX(2) LW1(2) LW2(0) LW2(1) LX(3)
            TLREC(3, 45);
        }
        bar_sync(0, 384);
        TLREC(3, 46);
        Conv c;
        {
            const uint32_t wsA = S_C + ((cw < 3) ? lane : 32 + (lane & 15)) * 4;
            const uint32_t wsB = S_C + ((cw < 2) ? lane : 32 + (lane & 15)) * 4;
            TLREC(3, 47);
            mbar_wait(S_WBAR + 40, 0);
            TLREC(3, 40);
            uint32_t t[52];
#pragma unroll
            for (int i = 0; i < 5; i++)
#pragma unroll
                for (int j = 0; j < 5; j++) {
                    uint32_t wa = lds32(wsA + (i * 5 + j) * CH * 2), wb = lds32(wsB + (i * 5 + j) * CH * 2);
                    if (i >= 1 && i <= 3 && j >= 1 && j <= 3) {
                        wa = badd(wa, lds32(wsA + (25 + (i - 1) * 3 + j - 1) * CH * 2));
                        wb = badd(wb, lds32(wsB + (25 + (i - 1) * 3 + j - 1) * CH * 2));
                    }
                    t[2 * (i * 5 + j)] = bmul(wb, WSC2);
                    t[2 * (i * 5 + j) + 1] = bmul(wa, WSC2);
                }
            t[50] = t[51] = 0;
            bar_sync(BAR_CV, 128);
            const uint32_t sc = S_C + (tid - 256) * 16;
#pragma unroll
            for (int k = 0; k < 13; k++) sts128(sc + k * 2048, t[4 * k], t[4 * k + 1], t[4 * k + 2], t[4 * k + 3]);
#pragma unroll
            for (int k = 0; k < 12; k++) lds128(c.w + 4 * k, sc + k * 2048);
            asm volatile("ld.shared.v2.b32 {%0,%1}, [%2];" : "=r"(c.w[48]), "=r"(c.w[49]) : "r"(sc + 12 * 2048));
            bar_sync(BAR_CV, 128);
        }
        const int mi = lane >> 3, qd = lane & 7;
        const int chA = (cw < 3) ? qd : 8 + (qd & 3), pxA = (cw < 3) ? 8 * cw : 16 * (qd >> 2);
        const int chB = (cw < 2) ? qd : 8 + (qd & 3), pxB = (cw < 2) ? 24 + 4 * cw : 16 * (qd >> 2) + 8 + 4 * (cw - 2);
        const uint32_t a1 = S_X + ((mi & 1) ? (pxB + (mi >> 1)) * (CH * 2) + chB * 16 : (pxA + 2 + (mi >> 1)) * (CH * 2) + chA * 16);
        const uint32_t a2 = S_X + (pxA + (mi & 1)) * (CH * 2) + chA * 16;
        const uint32_t sA = S_C + (pxA >> 4) * CGRP + ((pxA & 15) + mi) * CPITCH + chA * 16;
        const uint32_t sB = S_C + (pxB >> 4) * CGRP + ((pxB & 15) + mi) * CPITCH + chB * 16;
        auto nop = [] {};
        c.sink = CSINK;
        TLREC(3, 1);
        mbar_wait(S_BAR, 0);
        ldsm2s(c.xa[0], c.xa[1], a2);
        conv_ld<0>(c, a1); conv_ld<1>(c, a1); conv_ld<2>(c, a1); conv_ld<3>(c, a1);
        ldsm2s(c.xa[10], c.xa[11], a2 + 10 * CH * 2);
        TLREC(3, 41);
        conv_rest<0, 0>(c, a1 + XROW, a2 + XROW, nop);
        mbar_wait(S_BAR + 8, 0);
        TLREC(3, 42);
        conv_rest<0, 1>(c, a1 + XSTG, a2 + XSTG, nop);
        conv_rest<0, 2>(c, a1 + XSTG + XROW, a2 + XSTG + XROW, nop);
        TLREC(3, 2);
        bar_sync(BAR_CV, 128);
        const int xq = w0 - 2 + (cw & 1) * 18, yq = y0 - 2 + (cw >> 1);
        if (elect()) tma_x(&tmx, 0, cw, xq, yq + 8);
        mbar_wait(S_BAR + 16, 0);
        TLREC(3, 3);
        int t = 0;
        uint32_t p1 = a1 + 2 * XSTG, p2 = a2 + 2 * XSTG, qA = sA, qB = sB;
        int dq = CBUF;
#pragma unroll 1
        for (;;) {
            const uint32_t nb = S_BAR + 8 * ((t + 3) & (NS - 1)), np = ((t + 3) / NS) & 1;
            bool ok;
            conv_rest<0, 3>(c, p1, p2, nop);
            conv_out(c, qA, qB, [&] {
                bar_sync(BAR_EMPTY + (t & 1), 256);
                if (elect()) tma_x(&tmx, (t + 5) & (NS - 1), cw, xq, t + 5 < NSTG ? yq + 2 * (t + 5) : -8);
            });
            CFN(6)
            conv_rest<0, 3>(c, p1 + XROW, p2 + XROW, [&] { ok = mbar_test(nb, np); });
            conv_out(c, qA + 2 * CGRP, qB + 2 * CGRP, nop);
            bar_arrive(BAR_FULL + (t & 1), 256);
            TLREC(3, 4 + t);
            const int dp = (t & (NS - 1)) == 1 ? -(NS - 1) * XSTG : XSTG;
            p1 += dp; p2 += dp; qA += dq; qB += dq; dq = -dq;
            t++;
            if (__all_sync(0xffffffffu, ok) && t < NT - 1) continue;
            mbar_wait(nb, np);
            if (t == NT - 1) break;
        }
        conv_rest<2, 3>(c, p1, p2, nop);
        conv_out(c, qA, qB, [&] { bar_sync(BAR_EMPTY + 1, 256); });
        conv_rest<3, 3>(c, p1 + XROW, p2 + XROW, nop);
        conv_out(c, qA + 2 * CGRP, qB + 2 * CGRP, nop);
        bar_arrive(BAR_FULL + 1, 256);
        bar_arrive(BAR_EMPTY, 256);
        bar_arrive(BAR_EMPTY + 1, 256);
        mbar_wait(S_BAR + 8 * 2, 0);
        mbar_wait(S_BAR + 8 * 3, 0);
        if (CFT == 1 && c.sink == 0x12345) sts32(S_RED + 36, c.sink);
        TLREC(3, 35);
    } else {
        bar_sync(0, 384);
        const int wg = warp >> 2, wq = warp & 3;
        bar_arrive(BAR_EMPTY + wg, 256);
        if (wg == 0) {
            if (tid < 64) sts32(S_ST + tid * 4, tid < 32 ? 0x00003f80u : 0x3f800000u);
            const int kr = lane & 7;
#pragma unroll 1
            for (int i = 0; i < 3; i++) {
                const uint32_t base = S_W1 + (i * 4 + wq) * 6144;
                uint32_t r[12][4];
                mbar_wait(S_WBAR + 8 * i, 0);
                TLREC(3, 48 + i);
#pragma unroll
                for (int j = 0; j < 12; j++) lds128(r[j], base + kr * 768 + ((j >> 1) * 8 + ((kr + (j & 1) * 4 + (lane >> 3)) & 7)) * 16);
                __syncwarp();
#pragma unroll
                for (int j = 0; j < 12; j++)
                    sts128(base + kr * 16 + ((j >> 1) * 8 + ((kr + (j & 1) * 4 + (lane >> 3)) & 7)) * 128,
                           pack_h2(bf_lo(r[j][0]), bf_hi(r[j][0])), pack_h2(bf_lo(r[j][1]), bf_hi(r[j][1])),
                           pack_h2(bf_lo(r[j][2]), bf_hi(r[j][2])), pack_h2(bf_lo(r[j][3]), bf_hi(r[j][3])));
            }
        } else {
            constexpr int NW2 = 4 * (NWG - 1);
            uint32_t m = 0;
#pragma unroll 1
            for (int h = 0; h < 2; h++) {
                mbar_wait(S_WBAR + 24 + 8 * h, 0);
                if (wg == 1) TLREC(3, 51 + h);
#pragma unroll
                for (int j = 0; j < 72 / NW2; j++) {
                    uint32_t r[4];
                    lds128(r, S_W2 + h * (WBYTES / 2) + j * NW2 * 512 + (tid - 128) * 16);
                    m = habsmax(habsmax(m, r[0], r[1]), r[2], r[3]);
                }
            }
            m = __reduce_max_sync(0xffffffffu, max(m >> 16, m & 0xffffu));
            if (lane == 0) sts32(S_RED + (warp - 4) * 4, m);
            bar_sync(BAR_RED, 32 * NW2);
            m = __reduce_max_sync(0xffffffffu, lds32(S_RED + (lane & (NW2 - 1)) * 4));
            const int e = max(min(123 - (int)(m >> 7), 100), -15);
            const float wsc = __uint_as_float((uint32_t)(127 + e) << 23) * INV2A;
            if (tid == 128) sts32(S_RED + 32, ((uint32_t)(127 - e + (EPI == 1 ? 112 : 0)) << 7) * 0x10001u);
#pragma unroll 1
            for (int i = 0; i < 24 / NW2; i++) {
                const uint32_t base = S_W2 + (i * NW2 + warp - 4) * 3072;
                uint32_t r[6][4];
#pragma unroll
                for (int j = 0; j < 6; j++) lds128(r[j], base + (j / 3) * 1536 + (lane >> 2) * 192 + (j % 3) * 64 + (lane & 3) * 16);
                __syncwarp();
#pragma unroll
                for (int j = 0; j < 6; j++)
#pragma unroll
                    for (int k = 0; k < 4; k++)
                        sts32(base + (j / 3) * 1536 + ((j % 3) * 4 + k) * 128 + lane * 4, pack_h2(bf_lo(r[j][k]) * wsc, bf_hi(r[j][k]) * wsc));
            }
        }
        asm volatile("fence.proxy.async.shared::cta;" ::: "memory");
        TLREC(wg, 1);
        asm volatile("setmaxnreg.inc.sync.aligned.u32 %0;" ::"n"(REG_CONS));
        const uint32_t cbase = S_C + wq * CGRP + (lane & 15) * CPITCH + (lane >> 4) * 16;
        uint32_t goff = ((y0 + 2 * wg + (wq >> 1)) * IMG_W + w0 + (wq & 1) * 16 + (lane >> 2)) * (CH * 2) + (lane & 3) * 16;
        uint32_t H[96], a1[24], b[24], e[24], acc[24], res[24], st[2], sq[4], t[16], sink = lane;
        float sd[4];
        bool risky;
#pragma unroll
        for (int i = 0; i < 24; i++) { acc[i] = 0; res[i] = 0; }
        const uint32_t cb = cbase + wg * CBUF;
#define LDA(dst) _Pragma("unroll") for (int kk = 0; kk < 6; kk++) ldsm4(dst + 4 * kk, cb + kk * 32);
#define FETCH() { if (!LAST) { if (PEELT || i < NT / 2 - 1) bar_sync(BAR_FULL + wg, 256); LDA(b) } }
#define RELEASE() { if (!LAST && (PEELT || i < NT / 2 - 1)) bar_arrive(BAR_EMPTY + wg, 256); }
#define FULL() { if (i < NT / 2 - 1) bar_sync(BAR_FULL + wg, 256); }
#define LDB(k0, k1) { _Pragma("unroll") for (int kk = k0; kk < k1; kk++) ldsm4(b + 4 * kk, cb + kk * 32); }
#define GL(p) gelu<8>(H + 8 * (p))
#define GA8(p) { if (!LAST) gelu_a<8>(t, H + 8 * (p)); }
#define GB8(p) gelu_b<8>(H + 8 * (p), t)
#define G1(j, k0, k1) { if (!LAST || j != 0) gemm1<j, k0, k1>(H, a1, db); }
#define G2(k0, k1) gemm2<k0, k1>(acc, H, db)
#define P(ks, j, kk) G2(ks, ks + 1); G1(j, kk, kk + 1)
#define Q(j, kk, ks) G1(j, kk, kk + 1); G2(ks, ks + 1)
#define F wg_fence()
#define C wg_commit()
#define W(n) wg_wait<n>()
#define RDY(j) { if (!LAST || j != 0) pin<CN / 4>(H + (j) * (CN / 4)); }
#define CVT() epi_cvt(e, acc)
#define EO(r) epi_out<r>(e, res, osc2, out + gprev, i > 0)
#define RES(r) load_res<r>(res, x + gprev)
#define RESN(r) { if (!LAST) load_res<r>(res, x + goff); }
#define GN(w0, n) gelu<n>(H + (w0))
#define GAN(w0, n) { if (!LAST) gelu_a<n>(t, H + (w0)); }
#define GBN(w0, n) gelu_b<n>(H + (w0), t)
#define LO(i0, i1) { if (!LAST) ln_out<i0, i1>(a1, b, st); }
#define S SB1
#define LP(r) { if (!LAST) ln_part<r>(b, sq); }
#define LMC() { if (!LAST) { ln_mma(sd, sq, db); C; } }
#define RESL() { if (LAST) { load_res<0>(res, x + goff); load_res<1>(res, x + goff); } }
#define LF() { if (!LAST) risky = ln_fin(sd, st); }
#define LX2() { if (!LAST && __builtin_expect(risky, 0)) ln_fix(b, sd, st); }
        constexpr bool LAST = false;
        if (wg == 0) { bar_arrive(BAR_W1, 128 * NWG); bar_sync(BAR_W, 128); }
        else { bar_arrive(BAR_W2, 128 * NWG); bar_sync(BAR_W1, 128 * NWG); }
        TLREC(wg, 2);
        bar_sync(BAR_FULL + wg, 256);
        LDA(b)
        bar_arrive(BAR_EMPTY + wg, 256);
        TLREC(wg, 3);
        LP(0); LP(1); F; LMC(); W(0); LF(); LX2() LO(0, 24);
        TLREC(wg, 4);
        F; G1(0, 0, 6); C; W(0); RDY(0); GAN(0, T0);
        if (wg == 0) bar_sync(BAR_W2, 128 * NWG);
        const uint32_t osc2 = lds32(S_RED + 32);
        uint32_t gprev = goff;
#pragma unroll 1
        for (int i = 0; i < NT / 2 - PEELT; i++) {
            F; G1(1,0,6); C; RES(1); CVT(); GB8(0); GL(1); S
            F; G2(0,4); C; EO(0); GL(2); S
            W(1); RDY(1); F; Q(2,0,4); Q(2,1,5); G1(2,2,3); C; EO(1); GL(3); S
            FETCH()
            W(1); F; Q(2,3,6); Q(2,4,7); G1(2,5,6); C; GL(4); S
            W(1); F; G2(8,10); C; LP(0); LP(1); GL(5); S
            W(1); RDY(2); F; LMC(); Q(3,0,10); Q(3,1,11); G1(3,2,3); C; GL(6); S
            W(1); F; Q(3,3,12); Q(3,4,13); G1(3,5,6); C; LF(); GL(7); S
            LX2()
            W(1); F; G2(14,16); C; LO(0,12); GL(8); S
            W(1); RDY(3); F; Q(0,0,16); Q(0,1,17); G1(0,2,3); C; LO(12,24); GL(9); S
            RELEASE() RESL()
            W(1); F; Q(0,3,18); Q(0,4,19); G1(0,5,6); C; GL(10); S
            W(1); F; G2(20,22); C; GL(11); S
            W(1); RDY(0); F; G2(22,24); C; RESN(0); S GA8(0); S
            W(0); pin<24>(acc);
            gprev = goff;
            goff += TSTEP;
            TLREC(wg, 5 + i);
        }
        {
            const int i = 1;
            constexpr bool LAST = true;
            F; G1(1,0,6); C; RES(1); CVT(); GB8(0); GL(1); S
            F; G2(0,4); C; EO(0); GL(2); S
            W(1); RDY(1); F; Q(2,0,4); Q(2,1,5); G1(2,2,3); C; EO(1); GL(3); S
            FETCH()
            W(1); F; Q(2,3,6); Q(2,4,7); G1(2,5,6); C; GL(4); S
            W(1); F; G2(8,10); C; LP(0); LP(1); GL(5); S
            W(1); RDY(2); F; LMC(); Q(3,0,10); Q(3,1,11); G1(3,2,3); C; GL(6); S
            W(1); F; Q(3,3,12); Q(3,4,13); G1(3,5,6); C; LF(); GL(7); S
            LX2()
            W(1); F; G2(14,16); C; LO(0,12); GL(8); S
            W(1); RDY(3); F; Q(0,0,16); Q(0,1,17); G1(0,2,3); C; LO(12,24); GL(9); S
            RELEASE() RESL()
            W(1); F; Q(0,3,18); Q(0,4,19); G1(0,5,6); C; GL(10); S
            W(1); F; G2(20,22); C; GL(11); S
            W(1); RDY(0); F; G2(22,24); C; RESN(0); S GA8(0); S
            W(0); pin<24>(acc);
            gprev = goff;
            TLREC(wg, 20);
            CVT(); EO(0); EO(1);
        }
        if (sink == 0x12345) sts32(S_RED + 36, sink);
        TLREC(wg, 77); TLRECG(wg, 79);
    }
}

typedef CUresult (*EncodeFn)(CUtensorMap*, CUtensorMapDataType, cuuint32_t, void*, const cuuint64_t*, const cuuint64_t*,
                             const cuuint32_t*, const cuuint32_t*, CUtensorMapInterleave, CUtensorMapSwizzle,
                             CUtensorMapL2promotion, CUtensorMapFloatOOBfill);

}

extern "C" void kernel_launch(void* const* d_in, const int* in_sizes, int n_in, void* d_out, int out_size) {
    static EncodeFn enc = nullptr;
    if (!enc) {
        void* fn = nullptr;
        cudaDriverEntryPointQueryResult qr;
        cudaGetDriverEntryPoint("cuTensorMapEncodeTiled", &fn, cudaEnableDefault, &qr);
        enc = (EncodeFn)fn;
        cudaFuncSetAttribute(replk_kernel, cudaFuncAttributeMaxDynamicSharedMemorySize, SMEM_BYTES);
    }
    CUtensorMap tm;
    const cuuint64_t gdim[3] = {CH, IMG_W, IMG_H};
    const cuuint64_t gstr[2] = {CH * 2, (cuuint64_t)IMG_W * CH * 2};
    const cuuint32_t box[3] = {CH, (SW + 4) / 2, 1};
    const cuuint32_t estr[3] = {1, 1, 1};
    enc(&tm, CU_TENSOR_MAP_DATA_TYPE_BFLOAT16, 3, d_in[0], gdim, gstr, box, estr, CU_TENSOR_MAP_INTERLEAVE_NONE,
        CU_TENSOR_MAP_SWIZZLE_NONE, CU_TENSOR_MAP_L2_PROMOTION_L2_256B, CU_TENSOR_MAP_FLOAT_OOB_FILL_NONE);
    replk_kernel<<<(IMG_W / SW) * (IMG_H / RB), 384, SMEM_BYTES>>>(
        tm, (const uint8_t*)d_in[0], (const uint8_t*)d_in[1], (const uint8_t*)d_in[2], (const uint8_t*)d_in[3],
        (const uint8_t*)d_in[4], (uint8_t*)d_out, (uint64_t)(128 >> 4) << 32);
}
```

```cpp
#include <cuda_runtime.h>
#include <cuda_bf16.h>
#include <cuda_fp16.h>
#include <cuda.h>
#include <stdint.h>

namespace {

constexpr int IMG_H = 512, IMG_W = 512, CH = 96, HID = 384;
constexpr int SW = 32;
constexpr int RB = 64;
constexpr int NT = RB / 2;
constexpr int NSTG = NT + 2;
constexpr int NS = 4;
constexpr int NB = 2;
#define REG_CONS 168
#define REG_CONV 168
#define CN 96
#define T0 8
#define EPI 2
#define LNCVT 0

constexpr int XROW = (SW + 4) * CH * 2;
constexpr int XSTG = 2 * XROW;
constexpr int CPITCH = 208;
constexpr int CGRP = 16 * CPITCH + 64;
constexpr int CBUF = 4 * CGRP;
constexpr int WBYTES = CH * HID * 2;
constexpr uint32_t SB = 1024;
constexpr uint32_t S_W1 = SB;
constexpr uint32_t S_W2 = S_W1 + WBYTES;
constexpr uint32_t S_X = S_W2 + WBYTES;
constexpr uint32_t S_C = S_X + NS * XSTG;
constexpr uint32_t S_BAR = S_C + NB * CBUF;
constexpr uint32_t S_WBAR = S_BAR + 8 * NS;
constexpr uint32_t S_RED = S_WBAR + 8 * 6;
constexpr uint32_t S_ST = (S_RED + 64 + 127) / 128 * 128;
constexpr int SMEM_BYTES = S_ST + 256 - SB;
static_assert(SMEM_BYTES <= 232448, "smem");

constexpr int NWG = 2;
constexpr int BAR_FULL = 1, BAR_EMPTY = 4, BAR_W = 6, BAR_RED = 7, BAR_CV = 8, BAR_PAIR = 9;

constexpr float GA = 0.3292034911525734f;
constexpr uint32_t GK2 = 0x40d940d9u;
constexpr float INV2A = 1.5188174288475842f;
constexpr uint32_t WSC2 = (uint32_t)(127 - 48) * 0x00800080u;
constexpr float LN_EPS = 1e-5f * 0x1p-96f;
constexpr float LN_OUT = GA * 0x1p-112f;

constexpr uint32_t D1 = (S_W1 >> 4) | ((48 * 128 >> 4) << 16);
constexpr uint32_t D3 = (S_ST >> 4) | ((128 >> 4) << 16);
constexpr uint32_t D2 = (S_W2 >> 4) | ((12 * 128 >> 4) << 16);

template <int SCALE_D> __device__ __forceinline__ void wg_n64_h(uint32_t* d, const uint32_t* a, uint64_t desc);
template <>
__device__ __forceinline__ void wg_n64_h<0>(uint32_t* d, const uint32_t* a, uint64_t desc) {
    asm volatile("wgmma.mma_async.sync.aligned.m64n64k16.f16.f16.f16 {"
        "%0,%1,%2,%3,%4,%5,%6,%7,%8,%9,%10,%11,%12,%13,%14,%15},"
        "{%16,%17,%18,%19}, %20, 0, 1, 1, 1;"
        : "=r"(d[0]), "=r"(d[1]), "=r"(d[2]), "=r"(d[3]), "=r"(d[4]), "=r"(d[5]), "=r"(d[6]), "=r"(d[7]),
          "=r"(d[8]), "=r"(d[9]), "=r"(d[10]), "=r"(d[11]), "=r"(d[12]), "=r"(d[13]), "=r"(d[14]), "=r"(d[15])
        : "r"(a[0]), "r"(a[1]), "r"(a[2]), "r"(a[3]), "l"(desc));
}
template <>
__device__ __forceinline__ void wg_n64_h<1>(uint32_t* d, const uint32_t* a, uint64_t desc) {
    asm volatile("wgmma.mma_async.sync.aligned.m64n64k16.f16.f16.f16 {"
        "%0,%1,%2,%3,%4,%5,%6,%7,%8,%9,%10,%11,%12,%13,%14,%15},"
        "{%16,%17,%18,%19}, %20, 1, 1, 1, 1;"
        : "+r"(d[0]), "+r"(d[1]), "+r"(d[2]), "+r"(d[3]), "+r"(d[4]), "+r"(d[5]), "+r"(d[6]), "+r"(d[7]),
          "+r"(d[8]), "+r"(d[9]), "+r"(d[10]), "+r"(d[11]), "+r"(d[12]), "+r"(d[13]), "+r"(d[14]), "+r"(d[15])
        : "r"(a[0]), "r"(a[1]), "r"(a[2]), "r"(a[3]), "l"(desc));
}
template <int SCALE_D> __device__ __forceinline__ void wg_n96_h(uint32_t* d, const uint32_t* a, uint64_t desc);
template <>
__device__ __forceinline__ void wg_n96_h<0>(uint32_t* d, const uint32_t* a, uint64_t desc) {
    asm volatile("wgmma.mma_async.sync.aligned.m64n96k16.f16.f16.f16 {"
        "%0,%1,%2,%3,%4,%5,%6,%7,%8,%9,%10,%11,%12,%13,%14,%15,"
        "%16,%17,%18,%19,%20,%21,%22,%23},"
        "{%24,%25,%26,%27}, %28, 0, 1, 1, 1;"
        : "=r"(d[0]), "=r"(d[1]), "=r"(d[2]), "=r"(d[3]), "=r"(d[4]), "=r"(d[5]), "=r"(d[6]), "=r"(d[7]),
          "=r"(d[8]), "=r"(d[9]), "=r"(d[10]), "=r"(d[11]), "=r"(d[12]), "=r"(d[13]), "=r"(d[14]), "=r"(d[15]),
          "=r"(d[16]), "=r"(d[17]), "=r"(d[18]), "=r"(d[19]), "=r"(d[20]), "=r"(d[21]), "=r"(d[22]), "=r"(d[23])
        : "r"(a[0]), "r"(a[1]), "r"(a[2]), "r"(a[3]), "l"(desc));
}
template <>
__device__ __forceinline__ void wg_n96_h<1>(uint32_t* d, const uint32_t* a, uint64_t desc) {
    asm volatile("wgmma.mma_async.sync.aligned.m64n96k16.f16.f16.f16 {"
        "%0,%1,%2,%3,%4,%5,%6,%7,%8,%9,%10,%11,%12,%13,%14,%15,"
        "%16,%17,%18,%19,%20,%21,%22,%23},"
        "{%24,%25,%26,%27}, %28, 1, 1, 1, 1;"
        : "+r"(d[0]), "+r"(d[1]), "+r"(d[2]), "+r"(d[3]), "+r"(d[4]), "+r"(d[5]), "+r"(d[6]), "+r"(d[7]),
          "+r"(d[8]), "+r"(d[9]), "+r"(d[10]), "+r"(d[11]), "+r"(d[12]), "+r"(d[13]), "+r"(d[14]), "+r"(d[15]),
          "+r"(d[16]), "+r"(d[17]), "+r"(d[18]), "+r"(d[19]), "+r"(d[20]), "+r"(d[21]), "+r"(d[22]), "+r"(d[23])
        : "r"(a[0]), "r"(a[1]), "r"(a[2]), "r"(a[3]), "l"(desc));
}
template <int SCALE_D> __device__ __forceinline__ void wg_n128_h(uint32_t* d, const uint32_t* a, uint64_t desc);
template <>
__device__ __forceinline__ void wg_n128_h<0>(uint32_t* d, const uint32_t* a, uint64_t desc) {
    asm volatile("wgmma.mma_async.sync.aligned.m64n128k16.f16.f16.f16 {"
        "%0,%1,%2,%3,%4,%5,%6,%7,%8,%9,%10,%11,%12,%13,%14,%15,"
        "%16,%17,%18,%19,%20,%21,%22,%23,%24,%25,%26,%27,%28,%29,%30,%31},"
        "{%32,%33,%34,%35}, %36, 0, 1, 1, 1;"
        : "=r"(d[0]), "=r"(d[1]), "=r"(d[2]), "=r"(d[3]), "=r"(d[4]), "=r"(d[5]), "=r"(d[6]), "=r"(d[7]),
          "=r"(d[8]), "=r"(d[9]), "=r"(d[10]), "=r"(d[11]), "=r"(d[12]), "=r"(d[13]), "=r"(d[14]), "=r"(d[15]),
          "=r"(d[16]), "=r"(d[17]), "=r"(d[18]), "=r"(d[19]), "=r"(d[20]), "=r"(d[21]), "=r"(d[22]), "=r"(d[23]),
          "=r"(d[24]), "=r"(d[25]), "=r"(d[26]), "=r"(d[27]), "=r"(d[28]), "=r"(d[29]), "=r"(d[30]), "=r"(d[31])
        : "r"(a[0]), "r"(a[1]), "r"(a[2]), "r"(a[3]), "l"(desc));
}
template <>
__device__ __forceinline__ void wg_n128_h<1>(uint32_t* d, const uint32_t* a, uint64_t desc) {
    asm volatile("wgmma.mma_async.sync.aligned.m64n128k16.f16.f16.f16 {"
        "%0,%1,%2,%3,%4,%5,%6,%7,%8,%9,%10,%11,%12,%13,%14,%15,"
        "%16,%17,%18,%19,%20,%21,%22,%23,%24,%25,%26,%27,%28,%29,%30,%31},"
        "{%32,%33,%34,%35}, %36, 1, 1, 1, 1;"
        : "+r"(d[0]), "+r"(d[1]), "+r"(d[2]), "+r"(d[3]), "+r"(d[4]), "+r"(d[5]), "+r"(d[6]), "+r"(d[7]),
          "+r"(d[8]), "+r"(d[9]), "+r"(d[10]), "+r"(d[11]), "+r"(d[12]), "+r"(d[13]), "+r"(d[14]), "+r"(d[15]),
          "+r"(d[16]), "+r"(d[17]), "+r"(d[18]), "+r"(d[19]), "+r"(d[20]), "+r"(d[21]), "+r"(d[22]), "+r"(d[23]),
          "+r"(d[24]), "+r"(d[25]), "+r"(d[26]), "+r"(d[27]), "+r"(d[28]), "+r"(d[29]), "+r"(d[30]), "+r"(d[31])
        : "r"(a[0]), "r"(a[1]), "r"(a[2]), "r"(a[3]), "l"(desc));
}
template <int SCALE_D> __device__ __forceinline__ void wg_n192_h(uint32_t* d, const uint32_t* a, uint64_t desc);
template <>
__device__ __forceinline__ void wg_n192_h<0>(uint32_t* d, const uint32_t* a, uint64_t desc) {
    asm volatile("wgmma.mma_async.sync.aligned.m64n192k16.f16.f16.f16 {"
        "%0,%1,%2,%3,%4,%5,%6,%7,%8,%9,%10,%11,%12,%13,%14,%15,"
        "%16,%17,%18,%19,%20,%21,%22,%23,%24,%25,%26,%27,%28,%29,%30,%31,"
        "%32,%33,%34,%35,%36,%37,%38,%39,%40,%41,%42,%43,%44,%45,%46,%47},"
        "{%48,%49,%50,%51}, %52, 0, 1, 1, 1;"
        : "=r"(d[0]), "=r"(d[1]), "=r"(d[2]), "=r"(d[3]), "=r"(d[4]), "=r"(d[5]), "=r"(d[6]), "=r"(d[7]),
          "=r"(d[8]), "=r"(d[9]), "=r"(d[10]), "=r"(d[11]), "=r"(d[12]), "=r"(d[13]), "=r"(d[14]), "=r"(d[15]),
          "=r"(d[16]), "=r"(d[17]), "=r"(d[18]), "=r"(d[19]), "=r"(d[20]), "=r"(d[21]), "=r"(d[22]), "=r"(d[23]),
          "=r"(d[24]), "=r"(d[25]), "=r"(d[26]), "=r"(d[27]), "=r"(d[28]), "=r"(d[29]), "=r"(d[30]), "=r"(d[31]),
          "=r"(d[32]), "=r"(d[33]), "=r"(d[34]), "=r"(d[35]), "=r"(d[36]), "=r"(d[37]), "=r"(d[38]), "=r"(d[39]),
          "=r"(d[40]), "=r"(d[41]), "=r"(d[42]), "=r"(d[43]), "=r"(d[44]), "=r"(d[45]), "=r"(d[46]), "=r"(d[47])
        : "r"(a[0]), "r"(a[1]), "r"(a[2]), "r"(a[3]), "l"(desc));
}
template <>
__device__ __forceinline__ void wg_n192_h<1>(uint32_t* d, const uint32_t* a, uint64_t desc) {
    asm volatile("wgmma.mma_async.sync.aligned.m64n192k16.f16.f16.f16 {"
        "%0,%1,%2,%3,%4,%5,%6,%7,%8,%9,%10,%11,%12,%13,%14,%15,"
        "%16,%17,%18,%19,%20,%21,%22,%23,%24,%25,%26,%27,%28,%29,%30,%31,"
        "%32,%33,%34,%35,%36,%37,%38,%39,%40,%41,%42,%43,%44,%45,%46,%47},"
        "{%48,%49,%50,%51}, %52, 1, 1, 1, 1;"
        : "+r"(d[0]), "+r"(d[1]), "+r"(d[2]), "+r"(d[3]), "+r"(d[4]), "+r"(d[5]), "+r"(d[6]), "+r"(d[7]),
          "+r"(d[8]), "+r"(d[9]), "+r"(d[10]), "+r"(d[11]), "+r"(d[12]), "+r"(d[13]), "+r"(d[14]), "+r"(d[15]),
          "+r"(d[16]), "+r"(d[17]), "+r"(d[18]), "+r"(d[19]), "+r"(d[20]), "+r"(d[21]), "+r"(d[22]), "+r"(d[23]),
          "+r"(d[24]), "+r"(d[25]), "+r"(d[26]), "+r"(d[27]), "+r"(d[28]), "+r"(d[29]), "+r"(d[30]), "+r"(d[31]),
          "+r"(d[32]), "+r"(d[33]), "+r"(d[34]), "+r"(d[35]), "+r"(d[36]), "+r"(d[37]), "+r"(d[38]), "+r"(d[39]),
          "+r"(d[40]), "+r"(d[41]), "+r"(d[42]), "+r"(d[43]), "+r"(d[44]), "+r"(d[45]), "+r"(d[46]), "+r"(d[47])
        : "r"(a[0]), "r"(a[1]), "r"(a[2]), "r"(a[3]), "l"(desc));
}

#define HINT 0
constexpr uint64_t POL_EF = 0x12F0000000000000ull;
__device__ __forceinline__ void wg_fence() { asm volatile("wgmma.fence.sync.aligned;" ::: "memory"); }
__device__ __forceinline__ void wg_commit() { asm volatile("wgmma.commit_group.sync.aligned;" ::: "memory"); }
template <int N> __device__ __forceinline__ void wg_wait() { asm volatile("wgmma.wait_group.sync.aligned %0;" ::"n"(N) : "memory"); }
template <int N> __device__ __forceinline__ void pin(uint32_t* r) {
#pragma unroll
    for (int i = 0; i < N; i++) asm volatile("" : "+r"(r[i])::"memory");
}
__device__ __forceinline__ void sbar() { asm volatile("griddepcontrol.launch_dependents;" ::: "memory"); }

#define CK64 0
__device__ __forceinline__ void cfence(uint32_t& sink) {
    uint32_t ck;
    asm volatile("mov.u32 %0, %%clock;" : "=r"(ck)::"memory");
    sink ^= ck;
}
#define SFT 0
__device__ __forceinline__ void bar_sync(int id, int n) { asm volatile("bar.sync %0, %1;" ::"r"(id), "r"(n) : "memory"); }
__device__ __forceinline__ void bar_arrive(int id, int n) { asm volatile("bar.arrive %0, %1;" ::"r"(id), "r"(n) : "memory"); }
__device__ __forceinline__ void mbar_init(uint32_t a, uint32_t cnt) { asm volatile("mbarrier.init.shared::cta.b64 [%0], %1;" ::"r"(a), "r"(cnt) : "memory"); }
__device__ __forceinline__ void mbar_expect_tx(uint32_t a, uint32_t bytes) { asm volatile("mbarrier.arrive.expect_tx.shared::cta.b64 _, [%0], %1;" ::"r"(a), "r"(bytes) : "memory"); }
__device__ __forceinline__ bool mbar_try(uint32_t a, uint32_t parity) {
    uint32_t ok;
    asm volatile("{.reg .pred p; mbarrier.try_wait.parity.shared::cta.b64 p, [%1], %2; selp.u32 %0, 1, 0, p;}" : "=r"(ok) : "r"(a), "r"(parity) : "memory");
    return ok;
}
__device__ __forceinline__ void mbar_wait(uint32_t a, uint32_t parity) {
    asm volatile("{.reg .pred p, q; .reg .u32 g; mov.u32 g, 0;\n"
                 "L: mbarrier.try_wait.parity.shared::cta.b64 p, [%0], %1;\n"
                 "add.u32 g, g, 1; setp.lt.and.u32 q, g, 0x400000, !p; @q bra L;}" ::"r"(a), "r"(parity) : "memory");
}
__device__ __forceinline__ bool mbar_test(uint32_t a, uint32_t parity) {
    uint32_t ok;
    asm volatile("{.reg .pred p; mbarrier.test_wait.parity.shared::cta.b64 p, [%1], %2; selp.u32 %0, 1, 0, p;}" : "=r"(ok) : "r"(a), "r"(parity) : "memory");
    return ok;
}
__device__ __forceinline__ bool elect() {
    uint32_t ok;
    asm volatile("{.reg .pred p; elect.sync _|p, 0xffffffff; selp.u32 %0, 1, 0, p;}" : "=r"(ok));
    return ok;
}
__device__ __forceinline__ void tma_x(const CUtensorMap* tm, int slot, int q, int xq, int yq) {
    const uint32_t bar = S_BAR + 8 * slot;
    mbar_expect_tx(bar, XSTG / 4);
    asm volatile("cp.async.bulk.tensor.3d.shared::cluster.global.mbarrier::complete_tx::bytes [%0], [%1, {%3, %4, %5}], [%2];"
                 ::"r"(S_X + slot * XSTG + q * (XSTG / 4)), "l"(tm), "r"(bar), "r"(0), "r"(xq), "r"(yq) : "memory");
}
__device__ __forceinline__ void bulk_load(uint32_t dst, const void* src, uint32_t bytes, uint32_t bar) {
    asm volatile("cp.async.bulk.shared::cluster.global.mbarrier::complete_tx::bytes [%0], [%1], %2, [%3];"
                 ::"r"(dst), "l"(src), "r"(bytes), "r"(bar) : "memory");
}
__device__ __forceinline__ uint32_t lds32(uint32_t a) { uint32_t v; asm volatile("ld.shared.b32 %0, [%1];" : "=r"(v) : "r"(a)); return v; }
__device__ __forceinline__ void lds128(uint32_t* r, uint32_t a) { asm volatile("ld.shared.v4.b32 {%0,%1,%2,%3}, [%4];" : "=r"(r[0]), "=r"(r[1]), "=r"(r[2]), "=r"(r[3]) : "r"(a)); }
__device__ __forceinline__ void sts32(uint32_t a, uint32_t v) { asm volatile("st.shared.b32 [%0], %1;" ::"r"(a), "r"(v)); }
__device__ __forceinline__ void sts128(uint32_t a, uint32_t x, uint32_t y, uint32_t z, uint32_t w) { asm volatile("st.shared.v4.b32 [%0], {%1,%2,%3,%4};" ::"r"(a), "r"(x), "r"(y), "r"(z), "r"(w)); }
__device__ __forceinline__ void ldsm4(uint32_t* r, uint32_t a) {
    asm volatile("ldmatrix.sync.aligned.m8n8.x4.shared.b16 {%0,%1,%2,%3}, [%4];" : "=r"(r[0]), "=r"(r[1]), "=r"(r[2]), "=r"(r[3]) : "r"(a));
}
__device__ __forceinline__ void ldsm4s(uint32_t& r0, uint32_t& r1, uint32_t& r2, uint32_t& r3, uint32_t a) {
    asm volatile("ldmatrix.sync.aligned.m8n8.x4.shared.b16 {%0,%1,%2,%3}, [%4];" : "=r"(r0), "=r"(r1), "=r"(r2), "=r"(r3) : "r"(a));
}
__device__ __forceinline__ void ldsm2s(uint32_t& r0, uint32_t& r1, uint32_t a) {
    asm volatile("ldmatrix.sync.aligned.m8n8.x2.shared.b16 {%0,%1}, [%2];" : "=r"(r0), "=r"(r1) : "r"(a));
}
__device__ __forceinline__ void stsm4(uint32_t a, const uint32_t* r) {
    asm volatile("stmatrix.sync.aligned.m8n8.x4.shared.b16 [%4], {%0,%1,%2,%3};" ::"r"(r[0]), "r"(r[1]), "r"(r[2]), "r"(r[3]), "r"(a));
}
__device__ __forceinline__ void ldg128(uint32_t* r, const void* p) {
    asm volatile("ld.global.nc.L1::no_allocate.v4.b32 {%0,%1,%2,%3}, [%4];" : "=r"(r[0]), "=r"(r[1]), "=r"(r[2]), "=r"(r[3]) : "l"(p));
}
__device__ __forceinline__ void stg128(void* p, uint32_t x, uint32_t y, uint32_t z, uint32_t w) {
    asm volatile("st.global.L1::no_allocate.v4.b32 [%0], {%1,%2,%3,%4};" ::"l"(p), "r"(x), "r"(y), "r"(z), "r"(w));
}
__device__ __forceinline__ uint32_t bfma(uint32_t a, uint32_t b, uint32_t c) { uint32_t d; asm("fma.rn.bf16x2 %0, %1, %2, %3;" : "=r"(d) : "r"(a), "r"(b), "r"(c)); return d; }
__device__ __forceinline__ uint32_t bmul(uint32_t a, uint32_t b) { uint32_t d; asm("mul.rn.bf16x2 %0, %1, %2;" : "=r"(d) : "r"(a), "r"(b)); return d; }
__device__ __forceinline__ uint32_t vfma(uint32_t a, uint32_t b, uint32_t c) { uint32_t d; asm volatile("fma.rn.bf16x2 %0, %1, %2, %3;" : "=r"(d) : "r"(a), "r"(b), "r"(c)); return d; }
__device__ __forceinline__ void vacc(uint32_t& d, uint32_t a, uint32_t b) { asm volatile("fma.rn.bf16x2 %0, %1, %2, %0;" : "+r"(d) : "r"(a), "r"(b)); }
__device__ __forceinline__ uint32_t vadd(uint32_t a, uint32_t b) { uint32_t d; asm volatile("add.rn.bf16x2 %0, %1, %2;" : "=r"(d) : "r"(a), "r"(b)); return d; }
__device__ __forceinline__ uint32_t vsub(uint32_t a, uint32_t b) { uint32_t d; asm volatile("sub.rn.bf16x2 %0, %1, %2;" : "=r"(d) : "r"(a), "r"(b)); return d; }
__device__ __forceinline__ uint32_t vmul(uint32_t a, uint32_t b) { uint32_t d; asm volatile("mul.rn.bf16x2 %0, %1, %2;" : "=r"(d) : "r"(a), "r"(b)); return d; }
__device__ __forceinline__ uint32_t badd(uint32_t a, uint32_t b) { uint32_t d; asm("add.rn.bf16x2 %0, %1, %2;" : "=r"(d) : "r"(a), "r"(b)); return d; }
__device__ __forceinline__ uint32_t habsmax(uint32_t a, uint32_t b) { uint32_t d; asm("max.xorsign.abs.bf16x2 %0, %1, %2;" : "=r"(d) : "r"(a), "r"(b)); return d; }
__device__ __forceinline__ float bf_lo2(uint32_t v) { return __uint_as_float(v << 16); }
__device__ __forceinline__ float bf_lo(uint32_t v) { uint32_t d; asm("prmt.b32 %0, %1, 0, 0x1044;" : "=r"(d) : "r"(v)); return __uint_as_float(d); }
__device__ __forceinline__ float bf_hi(uint32_t v) { return __uint_as_float(v & 0xffff0000u); }
__device__ __forceinline__ uint32_t pack_h2(float lo, float hi) { uint32_t d; asm("cvt.rn.f16x2.f32 %0, %1, %2;" : "=r"(d) : "f"(hi), "f"(lo)); return d; }
__device__ __forceinline__ uint32_t pack_b2(float lo, float hi) { uint32_t d; asm("cvt.rn.bf16x2.f32 %0, %1, %2;" : "=r"(d) : "f"(hi), "f"(lo)); return d; }

template <int N> __device__ __forceinline__ void gelu(uint32_t* h) {
#pragma unroll
    for (int i = 0; i < N; i++) {
        uint32_t p, u, t;
        asm("fma.rn.f16x2 %0, %1, %1, %2;" : "=r"(p) : "r"(h[i]), "r"(GK2));
        asm("mul.rn.f16x2 %0, %1, %2;" : "=r"(u) : "r"(h[i]), "r"(p));
        asm("tanh.approx.f16x2 %0, %1;" : "=r"(t) : "r"(u));
        asm("fma.rn.f16x2 %0, %1, %2, %1;" : "=r"(h[i]) : "r"(h[i]), "r"(t));
    }
    pin<N>(h);
}
template <int N> __device__ __forceinline__ void gelu_a(uint32_t* t, const uint32_t* h) {
#pragma unroll
    for (int i = 0; i < N; i++) {
        uint32_t p, u;
        asm("fma.rn.f16x2 %0, %1, %1, %2;" : "=r"(p) : "r"(h[i]), "r"(GK2));
        asm("mul.rn.f16x2 %0, %1, %2;" : "=r"(u) : "r"(h[i]), "r"(p));
        asm("tanh.approx.f16x2 %0, %1;" : "=r"(t[i]) : "r"(u));
    }
    pin<N>(t);
}
template <int N> __device__ __forceinline__ void gelu_b(uint32_t* h, const uint32_t* t) {
#pragma unroll
    for (int i = 0; i < N; i++) asm volatile("fma.rn.f16x2 %0, %1, %2, %1;" : "=r"(h[i]) : "r"(h[i]), "r"(t[i]));
}
#define RESCARRY 1
#define MIDW 12
#define OV 1
#define SB2 SB1
#define SB3 SB1
#define SB1 cfence(sink);

#define PEEL0 1
#define PEEL1 1
#define EDGE1 1
#define PRO 2
#define XFIRST 3
#define XSECOND 3
#define PEELT 1
#define CSINK lane
#define CFT 1
#define CORDER 1
template <int S, int P, int ILO, int IHI>
__device__ __forceinline__ void conv_col(uint32_t x, const uint32_t* w, uint32_t (&acc)[4][S], uint32_t (&o)[S]) {
#pragma unroll
    for (int j = 4; j >= 0; j--) {
        const int q = P - j;
        if (q < 0 || q >= S) continue;
#pragma unroll
        for (int i = IHI; i >= ILO; i--) {
            uint32_t& d = (i == 4) ? o[q] : acc[i == 4 ? 0 : 3 - i][q];
            const uint32_t ww = w[2 * (i * 5 + j)];
            if (j > 0) vacc(d, x, ww);
            else if (i == 4 && CORDER == 1) { d = acc[0][q]; vacc(d, x, ww); }
            else d = (i == 0) ? vmul(x, ww) : vfma(x, ww, acc[i == 0 ? 0 : 4 - i][q]);
        }
    }
}
#define CFENCE 0x1d4
#define FFB 1
struct Conv {
    uint32_t w[50];
    uint32_t sA[10], sB[10];
    uint32_t accA[4][8], accB[4][4];
    uint32_t sink;
    uint32_t xa[2][12], xb[2][8];
};
template <int S, int P, int MODE, int WS>
__device__ __forceinline__ void tap_col(uint32_t x, const uint32_t* w, uint32_t (&d)[S], const uint32_t (&src)[S]) {
#pragma unroll
    for (int j = 4; j >= 0; j--) {
        const int q = P - j;
        if (q < 0 || q >= S) continue;
        if (j > 0 || MODE == 0) vacc(d[q], x, w[WS * j]);
        else if (MODE == 1) d[q] = vmul(x, w[0]);
        else d[q] = vfma(x, w[0], src[q]);
    }
}
template <int R, int K> __device__ __forceinline__ void conv_ld(Conv& c, uint32_t a1) {
    ldsm4s(c.xa[R][2 * K + 2], c.xb[R][2 * K], c.xa[R][2 * K + 3], c.xb[R][2 * K + 1], a1 + K * 2 * CH * 2);
}
#define CFN(n) { if ((CFENCE >> n) & 1) cfence(c.sink); }
#define ALLCOLS CA(0); CA(1); CA(2); CB(0); CA(3); CB(1); CA(4); CB(2); CA(5); CB(3); CA(6); CB(4); CA(7); CB(5); CA(8); CB(6); CA(9); CB(7); CA(10); CA(11);
template <int R, typename Fn>
__device__ __forceinline__ void conv_out(Conv& c, uint32_t sA, uint32_t sB, Fn before_store) {
    constexpr int RB_ = FFB ? R : 0;
#define CA(p) tap_col<8, p, 0, 2>(c.xa[R][p], c.w + 41, c.accA[R], c.accA[R])
#define CB(p) tap_col<4, p, 0, 2>(c.xb[R][p], c.w + 40, c.accB[RB_], c.accB[RB_])
    CA(0); CA(1); CA(2); CB(0); CA(3); CB(1); CA(4); CB(2); CA(5); CB(3); CA(6); CB(4); CA(7); CB(5);
    before_store();
    stsm4(sA, c.accA[R]);
    CA(8); CB(6); CA(9); CB(7); CA(10); CA(11);
    stsm4(sB, c.accB[RB_]);
    stsm4(sA + 4 * CPITCH, c.accA[R] + 4);
#undef CA
#undef CB
}
template <int S, int P, int R, bool OLD, bool NEW>
__device__ __forceinline__ void dcol(const uint32_t (&x)[2][S + 4], const uint32_t* w, uint32_t (&acc)[4][S]) {
    if (!OLD && !NEW) return;
    const uint32_t d = vsub(x[0][P], x[1][P]);
    if (R == 1) {
        if (OLD) tap_col<S, P, 0, 2>(d, w + 20, acc[0], acc[0]);
        if (NEW) tap_col<S, P, 2, 2>(d, w, acc[2], acc[3]);
    } else {
        if (OLD) tap_col<S, P, 0, 2>(d, w + 30, acc[1], acc[1]);
        if (NEW) tap_col<S, P, 0, 2>(d, w + 10, acc[3], acc[3]);
    }
}
template <int R, int ILO, int IHI, bool OLD, bool NEW, typename Fn>
__device__ __forceinline__ void conv_rest(Conv& c, uint32_t a1, uint32_t a2, Fn mid) {
    if (R == 1) {
        if (OLD) {
#define CA(p) tap_col<8, p, 1, 1>(c.xa[1][p], c.sA + 5, c.accA[0], c.accA[0])
#define CB(p) { if (FFB) tap_col<4, p, 1, 1>(c.xb[1][p], c.sB + 5, c.accB[0], c.accB[0]); }
            ALLCOLS
#undef CA
#undef CB
#pragma unroll
            for (int q = 0; q < 8; q++) { c.accA[1][q] = vadd(c.accA[3][q], c.accA[0][q]); c.accA[0][q] = vadd(c.accA[2][q], c.accA[0][q]); }
#pragma unroll
            for (int q = 0; q < 4 * FFB; q++) { c.accB[1][q] = vadd(c.accB[3][q], c.accB[0][q]); c.accB[0][q] = vadd(c.accB[2][q], c.accB[0][q]); }
            CFN(7)
        }
        if (NEW) {
#define CA(p) tap_col<8, p, 1, 1>(c.xa[1][p], c.sA, c.accA[3], c.accA[3])
#define CB(p) { if (FFB) tap_col<4, p, 1, 1>(c.xb[1][p], c.sB, c.accB[3], c.accB[3]); }
            ALLCOLS
#undef CA
#undef CB
            CFN(8)
        }
    }
#define CA(p) dcol<8, p, R, OLD, NEW>(c.xa, c.w + 1, c.accA)
#define CB(p) { if (FFB) dcol<4, p, R, OLD, NEW>(c.xb, c.w, c.accB); }
    CA(0); CA(1); CFN(0)
    ldsm2s(c.xa[1 - R][0], c.xa[1 - R][1], a2);
    CA(2); CB(0); CA(3); CB(1); CFN(1)
    conv_ld<1 - R, 0>(c, a1);
    CA(4); CB(2); CA(5); CB(3); CFN(2)
    conv_ld<1 - R, 1>(c, a1);
    CA(6); CB(4); CA(7); CB(5); CFN(3)
    conv_ld<1 - R, 2>(c, a1);
    CA(8); CB(6); CA(9); CB(7); CFN(4)
    conv_ld<1 - R, 3>(c, a1);
    CA(10); CA(11); CFN(5)
    ldsm2s(c.xa[1 - R][10], c.xa[1 - R][11], a2 + 10 * CH * 2);
    mid();
    CFN(9)
#undef CA
#undef CB
    if (!FFB) {
        uint32_t oB[4];
#define CB(p) conv_col<4, p, ILO, IHI>(c.xb[R][p], c.w, c.accB, oB)
        CB(0); CB(1); CB(2); CB(3); CB(4); CB(5); CB(6); CB(7);
#undef CB
        CFN(10)
    }
}

__device__ __forceinline__ uint64_t mkd(uint64_t db, uint32_t lo) { uint64_t d; asm volatile("add.u64 %0, %1, %2;" : "=l"(d) : "l"(db), "l"((uint64_t)lo)); return d; }
template <int J, int K0, int K1> __device__ __forceinline__ void gemm1(uint32_t* H, const uint32_t* a1, uint64_t db) {
#pragma unroll
    for (int kk = K0; kk < K1; kk++) {
        const uint64_t d = mkd(db, D1 + ((2 * kk * 48 + J * (CN / 8)) * 128 >> 4));
        if (kk == 0) wg_n96_h<0>(H + J * 24, a1, d);
        else wg_n96_h<1>(H + J * 24, a1 + 4 * kk, d);
    }
}
template <int K0, int K1> __device__ __forceinline__ void gemm2(uint32_t* acc, const uint32_t* H, uint64_t db) {
#pragma unroll
    for (int ks = K0; ks < K1; ks++) {
        const uint64_t d = mkd(db, D2 + (2 * ks * 12 * 128 >> 4));
        if (ks == 0) wg_n96_h<0>(acc, H, d);
        else wg_n96_h<1>(acc, H + 4 * ks, d);
    }
}

__device__ __forceinline__ float quad_sum(uint32_t v) {
    float s = bf_lo(v) + bf_hi(v);
    s += __shfl_xor_sync(0xffffffffu, s, 1);
    s += __shfl_xor_sync(0xffffffffu, s, 2);
    return s;
}
template <int r> __device__ __forceinline__ void ln_part(const uint32_t* a, uint32_t* sq) {
    uint32_t s[6], q[2];
#pragma unroll
    for (int i = 0; i < 6; i++) s[i] = badd(a[4 * i + r], a[4 * i + 2 + r]);
    sq[r] = badd(badd(badd(s[0], s[1]), badd(s[2], s[3])), badd(s[4], s[5]));
#pragma unroll
    for (int i = 0; i < 12; i++) q[i & 1] = (i < 2) ? bmul(a[2 * i + r], a[2 * i + r]) : bfma(a[2 * i + r], a[2 * i + r], q[i & 1]);
    sq[2 + r] = badd(q[0], q[1]);
    pin<1>(sq + r); pin<1>(sq + 2 + r);
}
__device__ __forceinline__ void ln_mma(float* d, const uint32_t* sq, uint64_t db) {
    asm volatile("wgmma.mma_async.sync.aligned.m64n8k16.f32.bf16.bf16 {%0,%1,%2,%3}, {%4,%5,%6,%7}, %8, 0, 1, 1, 1;"
                 : "=f"(d[0]), "=f"(d[1]), "=f"(d[2]), "=f"(d[3]) : "r"(sq[0]), "r"(sq[1]), "r"(sq[2]), "r"(sq[3]), "l"(mkd(db, D3)));
}
__device__ __forceinline__ uint32_t ln_pack(float v, float m) {
    float rs;
    asm("rsqrt.approx.ftz.f32 %0, %1;" : "=f"(rs) : "f"(v));
    rs *= LN_OUT;
    return pack_b2(rs, m * rs);
}
__device__ __forceinline__ bool ln_fin(float* d, uint32_t* st) {
    asm volatile("" : "+f"(d[0]), "+f"(d[1]), "+f"(d[2]), "+f"(d[3])::"memory");
    bool risky = false;
#pragma unroll
    for (int r = 0; r < 2; r++) {
        const float m = d[2 * r] * (-1.f / CH);
        const float t = fmaf(d[2 * r + 1], 1.f / CH, LN_EPS);
        const float v = fmaf(-m, m, t);
        risky |= !(v + v >= t);
        st[r] = ln_pack(v, m);
        d[2 * r] = m;
    }
    pin<2>(st);
    return __any_sync(0xffffffffu, risky);
}
__device__ __forceinline__ void ln_fix(uint32_t* a, const float* d, uint32_t* st) {
#pragma unroll
    for (int r = 0; r < 2; r++) {
        const uint32_t m2 = pack_b2(d[2 * r], d[2 * r]);
        uint32_t q[2];
#pragma unroll
        for (int i = 0; i < 12; i++) {
            a[2 * i + r] = badd(a[2 * i + r], m2);
            q[i & 1] = (i < 2) ? bmul(a[2 * i + r], a[2 * i + r]) : bfma(a[2 * i + r], a[2 * i + r], q[i & 1]);
        }
        st[r] = ln_pack(fmaf(quad_sum(badd(q[0], q[1])), 1.f / CH, LN_EPS), 0.f);
    }
}
template <int I0, int I1> __device__ __forceinline__ void ln_out(uint32_t* a, const uint32_t* b, const uint32_t* st) {
#pragma unroll
    for (int i = I0; i < I1; i++) {
        uint32_t v;
        asm("{.reg .b16 l, h; .reg .b32 ll, hh; mov.b32 {l, h}, %2; mov.b32 ll, {l, l}; mov.b32 hh, {h, h}; fma.rn.bf16x2 %0, %1, ll, hh;}"
            : "=r"(v) : "r"(b[i]), "r"(st[i & 1]));
        a[i] = v + 7u * (v & 0x7fff7fffu);
        pin<1>(a + i);
    }
}

__device__ __forceinline__ void epi_cvt(uint32_t* e, const uint32_t* acc) {
#pragma unroll
    for (int i = 0; i < 24; i++) {
        const uint32_t hv = acc[i];
        const float2 f = __half22float2(*reinterpret_cast<const __half2*>(&hv));
        e[i] = pack_b2(f.x, f.y);
    }
    pin<24>(e);
}
template <int R> __device__ __forceinline__ void epi_out(const uint32_t* e, const uint32_t* res, uint32_t osc2, uint8_t* gp, bool on) {
#pragma unroll
    for (int i = 0; i < 3; i++) {
        uint32_t o[4];
#pragma unroll
        for (int jj = 0; jj < 4; jj++) o[jj] = vfma(e[2 * (4 * i + jj) + R], osc2, res[(R * 3 + i) * 4 + jj]);
        asm volatile("{.reg .pred p; setp.ne.u32 p, %5, 0; @p st.global.L1::no_allocate.v4.b32 [%0], {%1,%2,%3,%4};}"
                     ::"l"(gp + R * 8 * CH * 2 + i * 64), "r"(o[0]), "r"(o[1]), "r"(o[2]), "r"(o[3]), "r"((uint32_t)(on && (!(HINT & 8) || osc2 == 0))));
    }
}
template <int R> __device__ __forceinline__ void load_res(uint32_t* res, const uint8_t* xg) {
#pragma unroll
    for (int i = 0; i < 3; i++) ldg128(res + (R * 3 + i) * 4, xg + R * 8 * CH * 2 + i * 64);
}

#define TLREC(role, idx)
#define TLRECG(role, idx)

constexpr int TSTEP = 2 * NWG * IMG_W * CH * 2;

__global__ void __launch_bounds__(384, 1)
replk_kernel(const __grid_constant__ CUtensorMap tmx, const uint8_t* __restrict__ x, const uint8_t* __restrict__ dwl,
             const uint8_t* __restrict__ dws, const uint8_t* __restrict__ w1, const uint8_t* __restrict__ w2,
             uint8_t* __restrict__ out, const uint64_t db) {
    extern __shared__ __align__(1024) uint8_t smem[];
#define ROT 2
    const int tid = (threadIdx.x + ROT * 128) % 384, lane = tid & 31;
    const int warp = __shfl_sync(0xffffffffu, tid >> 5, 0);
    const int w0 = (blockIdx.x % (IMG_W / SW)) * SW, y0 = (blockIdx.x / (IMG_W / SW)) * RB;
    if (warp < 8) { TLREC(warp >> 2, 0); TLRECG(warp >> 2, 78); }

    if (warp >= 8) {
        const int cw = warp - 8;
        if (cw == 0 && elect()) {
            if ((uint32_t)__cvta_generic_to_shared(smem) != SB) __trap();
#pragma unroll
            for (int s = 0; s < NS; s++) mbar_init(S_BAR + 8 * s, 4);
            mbar_init(S_WBAR + 40, 1);
            asm volatile("fence.mbarrier_init.release.cluster;" ::: "memory");
            TLREC(3, 43);
            mbar_expect_tx(S_WBAR + 40, 34 * CH * 2);
            bulk_load(S_C, dws, 25 * CH * 2, S_WBAR + 40);
            bulk_load(S_C + 25 * CH * 2, dwl, 9 * CH * 2, S_WBAR + 40);
            TLREC(3, 44);
        }
        bar_sync(BAR_CV, 128);
        const int xq = w0 - 2 + (cw & 1) * 18, yq = y0 - 2 + (cw >> 1);
        if (elect()) {
#pragma unroll
            for (int s = 0; s < XFIRST; s++) tma_x(&tmx, s, cw, xq, yq + 2 * s);
        }
        TLREC(3, 45);
        if (PRO & 1) bar_arrive(0, 160);
        Conv c;
        {
            const uint32_t wsA = S_C + ((cw < 3) ? lane : 32 + (lane & 15)) * 4;
            const uint32_t wsB = S_C + ((cw < 2) ? lane : 32 + (lane & 15)) * 4;
            TLREC(3, 47);
            mbar_wait(S_WBAR + 40, 0);
            TLREC(3, 40);
            uint32_t t[52];
#pragma unroll
            for (int i = 0; i < 5; i++)
#pragma unroll
                for (int j = 0; j < 5; j++) {
                    uint32_t wa = lds32(wsA + (i * 5 + j) * CH * 2), wb = lds32(wsB + (i * 5 + j) * CH * 2);
                    if (i >= 1 && i <= 3 && j >= 1 && j <= 3) {
                        wa = badd(wa, lds32(wsA + (25 + (i - 1) * 3 + j - 1) * CH * 2));
                        wb = badd(wb, lds32(wsB + (25 + (i - 1) * 3 + j - 1) * CH * 2));
                    }
                    t[2 * (i * 5 + j)] = bmul(wb, WSC2);
                    t[2 * (i * 5 + j) + 1] = bmul(wa, WSC2);
                }
            t[50] = t[51] = 0;
            if (elect()) {
#pragma unroll
                for (int s = XFIRST; s < XSECOND; s++) tma_x(&tmx, s, cw, xq, yq + 2 * s);
            }
            bar_sync(BAR_CV, 128);
            const uint32_t sc = S_C + (tid - 256) * 16;
#pragma unroll
            for (int k = 0; k < 13; k++) sts128(sc + k * 2048, t[4 * k], t[4 * k + 1], t[4 * k + 2], t[4 * k + 3]);
#pragma unroll
            for (int k = 0; k < 12; k++) lds128(c.w + 4 * k, sc + k * 2048);
            asm volatile("ld.shared.v2.b32 {%0,%1}, [%2];" : "=r"(c.w[48]), "=r"(c.w[49]) : "r"(sc + 12 * 2048));
            bar_sync(BAR_CV, 128);
        }
#pragma unroll
        for (int j = 0; j < 5; j++) {
            c.sA[j] = badd(c.w[2 * j + 1], c.w[2 * (5 + j) + 1]); c.sA[5 + j] = badd(c.w[2 * (10 + j) + 1], c.w[2 * (15 + j) + 1]);
            c.sB[j] = badd(c.w[2 * j], c.w[2 * (5 + j)]); c.sB[5 + j] = badd(c.w[2 * (10 + j)], c.w[2 * (15 + j)]);
        }
        pin<10>(c.sA);
        if (FFB) pin<10>(c.sB);
        const int mi = lane >> 3, qd = lane & 7;
        const int chA = (cw < 3) ? qd : 8 + (qd & 3), pxA = (cw < 3) ? 8 * cw : 16 * (qd >> 2);
        const int chB = (cw < 2) ? qd : 8 + (qd & 3), pxB = (cw < 2) ? 24 + 4 * cw : 16 * (qd >> 2) + 8 + 4 * (cw - 2);
        const uint32_t a1 = S_X + ((mi & 1) ? (pxB + (mi >> 1)) * (CH * 2) + chB * 16 : (pxA + 2 + (mi >> 1)) * (CH * 2) + chA * 16);
        const uint32_t a2 = S_X + (pxA + (mi & 1)) * (CH * 2) + chA * 16;
        const uint32_t sA = S_C + (pxA >> 4) * CGRP + ((pxA & 15) + mi) * CPITCH + chA * 16;
        const uint32_t sB = S_C + (pxB >> 4) * CGRP + ((pxB & 15) + mi) * CPITCH + chB * 16;
        auto nop = [] {};
        c.sink = CSINK;
        TLREC(3, 1);
        mbar_wait(S_BAR, 0);
        ldsm2s(c.xa[0][0], c.xa[0][1], a2);
        conv_ld<0, 0>(c, a1); conv_ld<0, 1>(c, a1); conv_ld<0, 2>(c, a1); conv_ld<0, 3>(c, a1);
        ldsm2s(c.xa[0][10], c.xa[0][11], a2 + 10 * CH * 2);
        TLREC(3, 41);
        conv_rest<0, 0, 0, false, false>(c, a1 + XROW, a2 + XROW, nop);
        if (elect()) {
#pragma unroll
            for (int s = XSECOND; s < 4; s++) tma_x(&tmx, s, cw, xq, yq + 2 * s);
        }
        mbar_wait(S_BAR + 8, 0);
        TLREC(3, 42);
        conv_rest<1, 0, 1, false, true>(c, a1 + XSTG, a2 + XSTG, nop);
        conv_rest<0, 0, 2, false, true>(c, a1 + XSTG + XROW, a2 + XSTG + XROW, nop);
        TLREC(3, 2);
        bar_sync(BAR_CV, 128);
        if (elect()) tma_x(&tmx, 0, cw, xq, yq + 8);
        mbar_wait(S_BAR + 16, 0);
        TLREC(3, 3);
        int t = 0;
        uint32_t p1 = a1 + 2 * XSTG, p2 = a2 + 2 * XSTG, qA = sA, qB = sB;
        int dq = CBUF;
#pragma unroll 1
        for (;;) {
            const uint32_t nb = S_BAR + 8 * ((t + 3) & (NS - 1)), np = ((t + 3) / NS) & 1;
            bool ok;
            conv_rest<1, 0, 3, true, true>(c, p1, p2, nop);
            conv_out<0>(c, qA, qB, [&] {
                bar_sync(BAR_EMPTY + (t & 1), 256);
                if (elect()) tma_x(&tmx, (t + 5) & (NS - 1), cw, xq, t + 5 < NSTG ? yq + 2 * (t + 5) : -8);
            });
            CFN(6)
            conv_rest<0, 0, 3, true, true>(c, p1 + XROW, p2 + XROW, [&] { ok = mbar_test(nb, np); });
            conv_out<1>(c, qA + 2 * CGRP, qB + 2 * CGRP, nop);
            bar_arrive(BAR_FULL + (t & 1), 256);
            TLREC(3, 4 + t);
            const int dp = (t & (NS - 1)) == 1 ? -(NS - 1) * XSTG : XSTG;
            p1 += dp; p2 += dp; qA += dq; qB += dq; dq = -dq;
            t++;
            if (__all_sync(0xffffffffu, ok) && t < NT - 1) continue;
            mbar_wait(nb, np);
            if (t == NT - 1) break;
        }
        conv_rest<1, 2, 3, true, false>(c, p1, p2, nop);
        conv_out<0>(c, qA, qB, [&] { bar_sync(BAR_EMPTY + 1, 256); });
        conv_rest<0, 3, 3, true, false>(c, p1 + XROW, p2 + XROW, nop);
        conv_out<1>(c, qA + 2 * CGRP, qB + 2 * CGRP, nop);
        bar_arrive(BAR_FULL + 1, 256);
        bar_arrive(BAR_EMPTY, 256);
        bar_arrive(BAR_EMPTY + 1, 256);
        mbar_wait(S_BAR + 8 * 2, 0);
        mbar_wait(S_BAR + 8 * 3, 0);
        if (CFT == 1 && c.sink == 0x12345) sts32(S_RED + 36, c.sink);
        TLREC(3, 35);
    } else {
        const int wg = warp >> 2, wq = warp & 3;
        if (warp == 0) {
            if (PRO & 1) bar_sync(0, 160);
            if (elect()) {
#pragma unroll
                for (int s = 0; s < 5; s++) mbar_init(S_WBAR + 8 * s, 1);
                asm volatile("fence.mbarrier_init.release.cluster;" ::: "memory");
#define LW1(i) { mbar_expect_tx(S_WBAR + 8 * i, WBYTES / 3); bulk_load(S_W1 + i * (WBYTES / 3), w1 + i * (WBYTES / 3), WBYTES / 3, S_WBAR + 8 * i); }
#define LW2(i) { mbar_expect_tx(S_WBAR + 24 + 8 * i, WBYTES / 2); bulk_load(S_W2 + i * (WBYTES / 2), w2 + i * (WBYTES / 2), WBYTES / 2, S_WBAR + 24 + 8 * i); }
                LW2(0) LW2(1)
                if (!(PRO & 2)) { LW1(0) LW1(1) LW1(2) }
                TLREC(3, 46);
            }
        }
        bar_arrive(BAR_EMPTY + wg, 256);
        if (tid < 64) sts32(S_ST + tid * 4, tid < 32 ? 0x00003f80u : 0x3f800000u);
        bar_sync(BAR_W, 256);
        uint32_t osc2;
        {
            uint32_t r[18][4], m = 0;
#pragma unroll
            for (int h = 0; h < 2; h++) {
                mbar_wait(S_WBAR + 24 + 8 * h, 0);
                if (wg == 1) TLREC(3, 51 + h);
                if ((PRO & 2) && h == 0 && warp == 0 && elect()) { LW1(0) LW1(1) LW1(2) }
#pragma unroll
                for (int j = 0; j < 9; j++) {
                    uint32_t* q = r[h * 9 + j];
                    lds128(q, S_W2 + h * (WBYTES / 2) + (warp * 3 + j / 3) * 1536 + (lane >> 2) * 192 + (j % 3) * 64 + (lane & 3) * 16);
                    m = habsmax(habsmax(m, q[0]), habsmax(habsmax(q[1], q[2]), q[3]));
                }
            }
            m &= 0x7fff7fffu;
            m = __reduce_max_sync(0xffffffffu, max(m >> 16, m & 0xffffu));
            if (lane == 0) sts32(S_RED + warp * 4, m);
            bar_sync(BAR_W, 256);
            m = __reduce_max_sync(0xffffffffu, lds32(S_RED + (lane & 7) * 4));
            const int e = max(min(123 - (int)(m >> 7), 100), -15);
            const float wsc = __uint_as_float((uint32_t)(127 + e) << 23) * INV2A;
            osc2 = ((uint32_t)(127 - e + (EPI == 1 ? 112 : 0)) << 7) * 0x10001u;
#pragma unroll
            for (int j = 0; j < 18; j++)
#pragma unroll
                for (int k = 0; k < 4; k++)
                    sts32(S_W2 + (j / 9) * (WBYTES / 2) + (warp * 3 + j % 9 / 3) * 1536 + ((j % 3) * 4 + k) * 128 + lane * 4,
                          pack_h2(bf_lo2(r[j][k]) * wsc, bf_hi(r[j][k]) * wsc));
        }
        if (wg == 1) TLREC(3, 53);
        {
            const int kr = lane & 7, nb = (kr + wg * 4 + (lane >> 3)) & 7;
#pragma unroll 1
            for (int i = 0; i < 3; i++) {
                const uint32_t base = S_W1 + (i * 4 + wq) * 6144;
                uint32_t r[6][4];
                mbar_wait(S_WBAR + 8 * i, 0);
                if (wg == 0) TLREC(3, 48 + i);
#pragma unroll
                for (int j = 0; j < 6; j++) lds128(r[j], base + kr * 768 + (j * 8 + nb) * 16);
                bar_sync(BAR_PAIR + wq, 64);
#pragma unroll
                for (int j = 0; j < 6; j++)
                    sts128(base + kr * 16 + (j * 8 + nb) * 128,
                           pack_h2(bf_lo2(r[j][0]), bf_hi(r[j][0])), pack_h2(bf_lo2(r[j][1]), bf_hi(r[j][1])),
                           pack_h2(bf_lo2(r[j][2]), bf_hi(r[j][2])), pack_h2(bf_lo2(r[j][3]), bf_hi(r[j][3])));
            }
        }
        asm volatile("fence.proxy.async.shared::cta;" ::: "memory");
        TLREC(wg, 1);
        const uint32_t cbase = S_C + wq * CGRP + (lane & 15) * CPITCH + (lane >> 4) * 16;
        uint32_t goff = ((y0 + 2 * wg + (wq >> 1)) * IMG_W + w0 + (wq & 1) * 16 + (lane >> 2)) * (CH * 2) + (lane & 3) * 16;
        uint32_t H[96], a1[24], b[24], e[24], acc[24], res[24], st[2], sq[4], t[16], sink = lane;
        float sd[4];
        bool risky;
#pragma unroll
        for (int i = 0; i < 24; i++) { acc[i] = 0; res[i] = 0; }
        const uint32_t cb = cbase + wg * CBUF;
#define LDA(dst) _Pragma("unroll") for (int kk = 0; kk < 6; kk++) ldsm4(dst + 4 * kk, cb + kk * 32);
#define FETCH() { if (!LAST) { if (PEELT || i < NT / 2 - 1) bar_sync(BAR_FULL + wg, 256); LDA(b) } }
#define RELEASE() { if (!LAST && (PEELT || i < NT / 2 - 1)) bar_arrive(BAR_EMPTY + wg, 256); }
#define FULL() { if (i < NT / 2 - 1) bar_sync(BAR_FULL + wg, 256); }
#define LDB(k0, k1) { _Pragma("unroll") for (int kk = k0; kk < k1; kk++) ldsm4(b + 4 * kk, cb + kk * 32); }
#define GL(p) gelu<8>(H + 8 * (p))
#define GA8(p) { if (!LAST) gelu_a<8>(t, H + 8 * (p)); }
#define GAF(p) gelu_a<8>(t, H + 8 * (p))
#define GB8(p) gelu_b<8>(H + 8 * (p), t)
#define G1(j, k0, k1) { if (!LAST || j != 0) gemm1<j, k0, k1>(H, a1, db); }
#define G2(k0, k1) gemm2<k0, k1>(acc, H, db)
#define P(ks, j, kk) G2(ks, ks + 1); G1(j, kk, kk + 1)
#define Q(j, kk, ks) G1(j, kk, kk + 1); G2(ks, ks + 1)
#define F wg_fence()
#define C wg_commit()
#define W(n) wg_wait<n>()
#define RDY(j) { if (!LAST || j != 0) pin<CN / 4>(H + (j) * (CN / 4)); }
#define CVT() epi_cvt(e, acc)
#define EO(r) epi_out<r>(e, res, osc2, out + gprev, i > 0)
#define RES(r) load_res<r>(res, x + gprev)
#define RESN(r) { if (!LAST) load_res<r>(res, x + goff); }
#define GN(w0, n) gelu<n>(H + (w0))
#define GAN(w0, n) { if (!LAST) gelu_a<n>(t, H + (w0)); }
#define GBN(w0, n) gelu_b<n>(H + (w0), t)
#define LO(i0, i1) { if (!LAST) ln_out<i0, i1>(a1, b, st); }
#define S SB1
#define LP(r) { if (!LAST) ln_part<r>(b, sq); }
#define LMC() { if (!LAST) { ln_mma(sd, sq, db); C; } }
#define RESL() { if (LAST) { load_res<0>(res, x + goff); load_res<1>(res, x + goff); } }
#define LF() { if (!LAST) risky = ln_fin(sd, st); }
#define LX2() { if (!LAST && __builtin_expect(risky, 0)) ln_fix(b, sd, st); }
        constexpr bool LAST = false;
        bar_sync(BAR_W, 256);
        TLREC(wg, 2);
        bar_sync(BAR_FULL + wg, 256);
        LDA(b)
        bar_arrive(BAR_EMPTY + wg, 256);
        TLREC(wg, 3);
        LP(0); LP(1); F; LMC(); W(0); LF(); LX2() LO(0, 24);
        TLREC(wg, 4);
        F; G1(0, 0, 6); C; W(0); RDY(0); GAN(0, T0);
        uint32_t gprev = goff;
#pragma unroll 1
        for (int i = 0; i < NT / 2 - PEELT; i++) {
            F; G1(1,0,6); C; CVT(); EO(0); EO(1); GB8(0); GL(1); S
            F; G2(0,4); C; GL(2); S
            W(1); RDY(1); F; Q(2,0,4); Q(2,1,5); G1(2,2,3); C; GL(3); S
            FETCH()
            W(1); F; Q(2,3,6); Q(2,4,7); G1(2,5,6); C; GL(4); S
            W(1); F; G2(8,10); C; LP(0); LP(1); GL(5); S
            W(1); RDY(2); F; LMC(); Q(3,0,10); Q(3,1,11); G1(3,2,3); C; GL(6); S
            W(1); F; Q(3,3,12); Q(3,4,13); G1(3,5,6); C; LF(); GL(7); S
            LX2()
            W(1); F; G2(14,16); C; LO(0,12); GL(8); S
            W(1); RDY(3); F; Q(0,0,16); Q(0,1,17); G1(0,2,3); C; LO(12,24); GL(9); S
            RELEASE() RESL()
            W(1); F; Q(0,3,18); Q(0,4,19); G1(0,5,6); C; RESN(0); GL(10); S
            W(1); F; G2(20,22); C; RESN(1); GL(11); S
            W(1); RDY(0); F; G2(22,24); C; S GA8(0); S
            W(0); pin<24>(acc);
            gprev = goff;
            goff += TSTEP;
            TLREC(wg, 5 + i);
        }
        {
            const int i = 1;
            constexpr bool LAST = true;
            F; G1(1,0,6); C; CVT(); EO(0); EO(1); GB8(0); GL(1); S
            F; G2(0,4); C; GL(2); S
            W(1); RDY(1); F; Q(2,0,4); Q(2,1,5); G1(2,2,3); C; GL(3); S
            FETCH()
            W(1); F; Q(2,3,6); Q(2,4,7); G1(2,5,6); C; GL(4); S
            W(1); F; G2(8,10); C; LP(0); LP(1); GL(5); S
            W(1); RDY(2); F; LMC(); Q(3,0,10); Q(3,1,11); G1(3,2,3); C; GL(6); S
            W(1); F; Q(3,3,12); Q(3,4,13); G1(3,5,6); C; LF(); GL(7); S
            LX2()
            W(1); F; G2(14,16); C; LO(0,12); GL(8); S
            W(1); RDY(3); F; Q(0,0,16); Q(0,1,17); G1(0,2,3); C; LO(12,24); GL(9); S
            RELEASE() RESL()
            W(1); F; Q(0,3,18); Q(0,4,19); G1(0,5,6); C; RESN(0); GL(10); S
            W(1); F; G2(20,22); C; RESN(1); GL(11); S
            W(1); RDY(0); F; G2(22,24); C; S GA8(0); S
            W(0); pin<24>(acc);
            gprev = goff;
            TLREC(wg, 20);
            CVT(); EO(0); EO(1);
        }
        if (sink == 0x12345) sts32(S_RED + 36, sink);
        TLREC(wg, 77); TLRECG(wg, 79);
    }
}

typedef CUresult (*EncodeFn)(CUtensorMap*, CUtensorMapDataType, cuuint32_t, void*, const cuuint64_t*, const cuuint64_t*,
                             const cuuint32_t*, const cuuint32_t*, CUtensorMapInterleave, CUtensorMapSwizzle,
                             CUtensorMapL2promotion, CUtensorMapFloatOOBfill);

}

extern "C" void kernel_launch(void* const* d_in, const int* in_sizes, int n_in, void* d_out, int out_size) {
    static EncodeFn enc = nullptr;
    if (!enc) {
        void* fn = nullptr;
        cudaDriverEntryPointQueryResult qr;
        cudaGetDriverEntryPoint("cuTensorMapEncodeTiled", &fn, cudaEnableDefault, &qr);
        enc = (EncodeFn)fn;
        cudaFuncSetAttribute(replk_kernel, cudaFuncAttributeMaxDynamicSharedMemorySize, SMEM_BYTES);
    }
    CUtensorMap tm;
    const cuuint64_t gdim[3] = {CH, IMG_W, IMG_H};
    const cuuint64_t gstr[2] = {CH * 2, (cuuint64_t)IMG_W * CH * 2};
    const cuuint32_t box[3] = {CH, (SW + 4) / 2, 1};
    const cuuint32_t estr[3] = {1, 1, 1};
    enc(&tm, CU_TENSOR_MAP_DATA_TYPE_BFLOAT16, 3, d_in[0], gdim, gstr, box, estr, CU_TENSOR_MAP_INTERLEAVE_NONE,
        CU_TENSOR_MAP_SWIZZLE_NONE, CU_TENSOR_MAP_L2_PROMOTION_L2_256B, CU_TENSOR_MAP_FLOAT_OOB_FILL_NONE);
    replk_kernel<<<(IMG_W / SW) * (IMG_H / RB), 384, SMEM_BYTES>>>(
        tm, (const uint8_t*)d_in[0], (const uint8_t*)d_in[1], (const uint8_t*)d_in[2], (const uint8_t*)d_in[3],
        (const uint8_t*)d_in[4], (uint8_t*)d_out, (uint64_t)(128 >> 4) << 32);
}
```

```cpp
#include <cuda_runtime.h>
#include <cuda_bf16.h>
#include <cuda_fp16.h>
#include <cuda.h>
#include <stdint.h>

namespace {

constexpr int IMG_H = 512, IMG_W = 512, CH = 96, HID = 384;
constexpr int SW = 32;
constexpr int RB = 64;
constexpr int NT = RB / 2;
constexpr int NSTG = NT + 2;
constexpr int NS = 4;
constexpr int NB = 2;
#define REG_CONS 168
#define REG_CONV 168
#define CN 96
#define T0 8
#define EPI 2
#define LNCVT 0

constexpr int XROW = (SW + 4) * CH * 2;
constexpr int XSTG = 2 * XROW;
constexpr int CPITCH = 208;
constexpr int CGRP = 16 * CPITCH + 64;
constexpr int CBUF = 4 * CGRP;
constexpr int WBYTES = CH * HID * 2;
constexpr uint32_t SB = 1024;
constexpr uint32_t S_W1 = SB;
constexpr uint32_t S_W2 = S_W1 + WBYTES;
constexpr uint32_t S_X = S_W2 + WBYTES;
constexpr uint32_t S_C = S_X + NS * XSTG;
constexpr uint32_t S_BAR = S_C + NB * CBUF;
constexpr uint32_t S_WBAR = S_BAR + 8 * NS;
constexpr uint32_t S_RED = S_WBAR + 8 * 6;
constexpr uint32_t S_ST = (S_RED + 64 + 127) / 128 * 128;
constexpr int SMEM_BYTES = S_ST + 256 - SB;
static_assert(SMEM_BYTES <= 232448, "smem");

constexpr int NWG = 2;
constexpr int BAR_FULL = 1, BAR_EMPTY = 4, BAR_W = 6, BAR_RED = 7, BAR_CV = 8, BAR_PAIR = 9;

constexpr float GA = 0.3292034911525734f;
constexpr uint32_t GK2 = 0x40d940d9u;
constexpr float INV2A = 1.5188174288475842f;
constexpr uint32_t WSC2 = (uint32_t)(127 - 48) * 0x00800080u;
constexpr float LN_EPS = 1e-5f * 0x1p-96f;
constexpr float LN_OUT = GA * 0x1p-112f;

constexpr uint32_t D1 = (S_W1 >> 4) | ((48 * 128 >> 4) << 16);
constexpr uint32_t D3 = (S_ST >> 4) | ((128 >> 4) << 16);
constexpr uint32_t D2 = (S_W2 >> 4) | ((12 * 128 >> 4) << 16);

template <int SCALE_D> __device__ __forceinline__ void wg_n64_h(uint32_t* d, const uint32_t* a, uint64_t desc);
template <>
__device__ __forceinline__ void wg_n64_h<0>(uint32_t* d, const uint32_t* a, uint64_t desc) {
    asm volatile("wgmma.mma_async.sync.aligned.m64n64k16.f16.f16.f16 {"
        "%0,%1,%2,%3,%4,%5,%6,%7,%8,%9,%10,%11,%12,%13,%14,%15},"
        "{%16,%17,%18,%19}, %20, 0, 1, 1, 1;"
        : "=r"(d[0]), "=r"(d[1]), "=r"(d[2]), "=r"(d[3]), "=r"(d[4]), "=r"(d[5]), "=r"(d[6]), "=r"(d[7]),
          "=r"(d[8]), "=r"(d[9]), "=r"(d[10]), "=r"(d[11]), "=r"(d[12]), "=r"(d[13]), "=r"(d[14]), "=r"(d[15])
        : "r"(a[0]), "r"(a[1]), "r"(a[2]), "r"(a[3]), "l"(desc));
}
template <>
__device__ __forceinline__ void wg_n64_h<1>(uint32_t* d, const uint32_t* a, uint64_t desc) {
    asm volatile("wgmma.mma_async.sync.aligned.m64n64k16.f16.f16.f16 {"
        "%0,%1,%2,%3,%4,%5,%6,%7,%8,%9,%10,%11,%12,%13,%14,%15},"
        "{%16,%17,%18,%19}, %20, 1, 1, 1, 1;"
        : "+r"(d[0]), "+r"(d[1]), "+r"(d[2]), "+r"(d[3]), "+r"(d[4]), "+r"(d[5]), "+r"(d[6]), "+r"(d[7]),
          "+r"(d[8]), "+r"(d[9]), "+r"(d[10]), "+r"(d[11]), "+r"(d[12]), "+r"(d[13]), "+r"(d[14]), "+r"(d[15])
        : "r"(a[0]), "r"(a[1]), "r"(a[2]), "r"(a[3]), "l"(desc));
}
template <int SCALE_D> __device__ __forceinline__ void wg_n96_h(uint32_t* d, const uint32_t* a, uint64_t desc);
template <>
__device__ __forceinline__ void wg_n96_h<0>(uint32_t* d, const uint32_t* a, uint64_t desc) {
    asm volatile("wgmma.mma_async.sync.aligned.m64n96k16.f16.f16.f16 {"
        "%0,%1,%2,%3,%4,%5,%6,%7,%8,%9,%10,%11,%12,%13,%14,%15,"
        "%16,%17,%18,%19,%20,%21,%22,%23},"
        "{%24,%25,%26,%27}, %28, 0, 1, 1, 1;"
        : "=r"(d[0]), "=r"(d[1]), "=r"(d[2]), "=r"(d[3]), "=r"(d[4]), "=r"(d[5]), "=r"(d[6]), "=r"(d[7]),
          "=r"(d[8]), "=r"(d[9]), "=r"(d[10]), "=r"(d[11]), "=r"(d[12]), "=r"(d[13]), "=r"(d[14]), "=r"(d[15]),
          "=r"(d[16]), "=r"(d[17]), "=r"(d[18]), "=r"(d[19]), "=r"(d[20]), "=r"(d[21]), "=r"(d[22]), "=r"(d[23])
        : "r"(a[0]), "r"(a[1]), "r"(a[2]), "r"(a[3]), "l"(desc));
}
template <>
__device__ __forceinline__ void wg_n96_h<1>(uint32_t* d, const uint32_t* a, uint64_t desc) {
    asm volatile("wgmma.mma_async.sync.aligned.m64n96k16.f16.f16.f16 {"
        "%0,%1,%2,%3,%4,%5,%6,%7,%8,%9,%10,%11,%12,%13,%14,%15,"
        "%16,%17,%18,%19,%20,%21,%22,%23},"
        "{%24,%25,%26,%27}, %28, 1, 1, 1, 1;"
        : "+r"(d[0]), "+r"(d[1]), "+r"(d[2]), "+r"(d[3]), "+r"(d[4]), "+r"(d[5]), "+r"(d[6]), "+r"(d[7]),
          "+r"(d[8]), "+r"(d[9]), "+r"(d[10]), "+r"(d[11]), "+r"(d[12]), "+r"(d[13]), "+r"(d[14]), "+r"(d[15]),
          "+r"(d[16]), "+r"(d[17]), "+r"(d[18]), "+r"(d[19]), "+r"(d[20]), "+r"(d[21]), "+r"(d[22]), "+r"(d[23])
        : "r"(a[0]), "r"(a[1]), "r"(a[2]), "r"(a[3]), "l"(desc));
}
template <int SCALE_D> __device__ __forceinline__ void wg_n128_h(uint32_t* d, const uint32_t* a, uint64_t desc);
template <>
__device__ __forceinline__ void wg_n128_h<0>(uint32_t* d, const uint32_t* a, uint64_t desc) {
    asm volatile("wgmma.mma_async.sync.aligned.m64n128k16.f16.f16.f16 {"
        "%0,%1,%2,%3,%4,%5,%6,%7,%8,%9,%10,%11,%12,%13,%14,%15,"
        "%16,%17,%18,%19,%20,%21,%22,%23,%24,%25,%26,%27,%28,%29,%30,%31},"
        "{%32,%33,%34,%35}, %36, 0, 1, 1, 1;"
        : "=r"(d[0]), "=r"(d[1]), "=r"(d[2]), "=r"(d[3]), "=r"(d[4]), "=r"(d[5]), "=r"(d[6]), "=r"(d[7]),
          "=r"(d[8]), "=r"(d[9]), "=r"(d[10]), "=r"(d[11]), "=r"(d[12]), "=r"(d[13]), "=r"(d[14]), "=r"(d[15]),
          "=r"(d[16]), "=r"(d[17]), "=r"(d[18]), "=r"(d[19]), "=r"(d[20]), "=r"(d[21]), "=r"(d[22]), "=r"(d[23]),
          "=r"(d[24]), "=r"(d[25]), "=r"(d[26]), "=r"(d[27]), "=r"(d[28]), "=r"(d[29]), "=r"(d[30]), "=r"(d[31])
        : "r"(a[0]), "r"(a[1]), "r"(a[2]), "r"(a[3]), "l"(desc));
}
template <>
__device__ __forceinline__ void wg_n128_h<1>(uint32_t* d, const uint32_t* a, uint64_t desc) {
    asm volatile("wgmma.mma_async.sync.aligned.m64n128k16.f16.f16.f16 {"
        "%0,%1,%2,%3,%4,%5,%6,%7,%8,%9,%10,%11,%12,%13,%14,%15,"
        "%16,%17,%18,%19,%20,%21,%22,%23,%24,%25,%26,%27,%28,%29,%30,%31},"
        "{%32,%33,%34,%35}, %36, 1, 1, 1, 1;"
        : "+r"(d[0]), "+r"(d[1]), "+r"(d[2]), "+r"(d[3]), "+r"(d[4]), "+r"(d[5]), "+r"(d[6]), "+r"(d[7]),
          "+r"(d[8]), "+r"(d[9]), "+r"(d[10]), "+r"(d[11]), "+r"(d[12]), "+r"(d[13]), "+r"(d[14]), "+r"(d[15]),
          "+r"(d[16]), "+r"(d[17]), "+r"(d[18]), "+r"(d[19]), "+r"(d[20]), "+r"(d[21]), "+r"(d[22]), "+r"(d[23]),
          "+r"(d[24]), "+r"(d[25]), "+r"(d[26]), "+r"(d[27]), "+r"(d[28]), "+r"(d[29]), "+r"(d[30]), "+r"(d[31])
        : "r"(a[0]), "r"(a[1]), "r"(a[2]), "r"(a[3]), "l"(desc));
}
template <int SCALE_D> __device__ __forceinline__ void wg_n192_h(uint32_t* d, const uint32_t* a, uint64_t desc);
template <>
__device__ __forceinline__ void wg_n192_h<0>(uint32_t* d, const uint32_t* a, uint64_t desc) {
    asm volatile("wgmma.mma_async.sync.aligned.m64n192k16.f16.f16.f16 {"
        "%0,%1,%2,%3,%4,%5,%6,%7,%8,%9,%10,%11,%12,%13,%14,%15,"
        "%16,%17,%18,%19,%20,%21,%22,%23,%24,%25,%26,%27,%28,%29,%30,%31,"
        "%32,%33,%34,%35,%36,%37,%38,%39,%40,%41,%42,%43,%44,%45,%46,%47},"
        "{%48,%49,%50,%51}, %52, 0, 1, 1, 1;"
        : "=r"(d[0]), "=r"(d[1]), "=r"(d[2]), "=r"(d[3]), "=r"(d[4]), "=r"(d[5]), "=r"(d[6]), "=r"(d[7]),
          "=r"(d[8]), "=r"(d[9]), "=r"(d[10]), "=r"(d[11]), "=r"(d[12]), "=r"(d[13]), "=r"(d[14]), "=r"(d[15]),
          "=r"(d[16]), "=r"(d[17]), "=r"(d[18]), "=r"(d[19]), "=r"(d[20]), "=r"(d[21]), "=r"(d[22]), "=r"(d[23]),
          "=r"(d[24]), "=r"(d[25]), "=r"(d[26]), "=r"(d[27]), "=r"(d[28]), "=r"(d[29]), "=r"(d[30]), "=r"(d[31]),
          "=r"(d[32]), "=r"(d[33]), "=r"(d[34]), "=r"(d[35]), "=r"(d[36]), "=r"(d[37]), "=r"(d[38]), "=r"(d[39]),
          "=r"(d[40]), "=r"(d[41]), "=r"(d[42]), "=r"(d[43]), "=r"(d[44]), "=r"(d[45]), "=r"(d[46]), "=r"(d[47])
        : "r"(a[0]), "r"(a[1]), "r"(a[2]), "r"(a[3]), "l"(desc));
}
template <>
__device__ __forceinline__ void wg_n192_h<1>(uint32_t* d, const uint32_t* a, uint64_t desc) {
    asm volatile("wgmma.mma_async.sync.aligned.m64n192k16.f16.f16.f16 {"
        "%0,%1,%2,%3,%4,%5,%6,%7,%8,%9,%10,%11,%12,%13,%14,%15,"
        "%16,%17,%18,%19,%20,%21,%22,%23,%24,%25,%26,%27,%28,%29,%30,%31,"
        "%32,%33,%34,%35,%36,%37,%38,%39,%40,%41,%42,%43,%44,%45,%46,%47},"
        "{%48,%49,%50,%51}, %52, 1, 1, 1, 1;"
        : "+r"(d[0]), "+r"(d[1]), "+r"(d[2]), "+r"(d[3]), "+r"(d[4]), "+r"(d[5]), "+r"(d[6]), "+r"(d[7]),
          "+r"(d[8]), "+r"(d[9]), "+r"(d[10]), "+r"(d[11]), "+r"(d[12]), "+r"(d[13]), "+r"(d[14]), "+r"(d[15]),
          "+r"(d[16]), "+r"(d[17]), "+r"(d[18]), "+r"(d[19]), "+r"(d[20]), "+r"(d[21]), "+r"(d[22]), "+r"(d[23]),
          "+r"(d[24]), "+r"(d[25]), "+r"(d[26]), "+r"(d[27]), "+r"(d[28]), "+r"(d[29]), "+r"(d[30]), "+r"(d[31]),
          "+r"(d[32]), "+r"(d[33]), "+r"(d[34]), "+r"(d[35]), "+r"(d[36]), "+r"(d[37]), "+r"(d[38]), "+r"(d[39]),
          "+r"(d[40]), "+r"(d[41]), "+r"(d[42]), "+r"(d[43]), "+r"(d[44]), "+r"(d[45]), "+r"(d[46]), "+r"(d[47])
        : "r"(a[0]), "r"(a[1]), "r"(a[2]), "r"(a[3]), "l"(desc));
}

#define HINT 0
constexpr uint64_t POL_EF = 0x12F0000000000000ull;
__device__ __forceinline__ void wg_fence() { asm volatile("wgmma.fence.sync.aligned;" ::: "memory"); }
__device__ __forceinline__ void wg_commit() { asm volatile("wgmma.commit_group.sync.aligned;" ::: "memory"); }
template <int N> __device__ __forceinline__ void wg_wait() { asm volatile("wgmma.wait_group.sync.aligned %0;" ::"n"(N) : "memory"); }
template <int N> __device__ __forceinline__ void pin(uint32_t* r) {
#pragma unroll
    for (int i = 0; i < N; i++) asm volatile("" : "+r"(r[i])::"memory");
}
__device__ __forceinline__ void sbar() { asm volatile("griddepcontrol.launch_dependents;" ::: "memory"); }

#define CK64 0
__device__ __forceinline__ void cfence(uint32_t& sink) {
    uint32_t ck;
    asm volatile("mov.u32 %0, %%clock;" : "=r"(ck)::"memory");
    sink ^= ck;
}
#define SFT 0
__device__ __forceinline__ void bar_sync(int id, int n) { asm volatile("bar.sync %0, %1;" ::"r"(id), "r"(n) : "memory"); }
__device__ __forceinline__ void bar_arrive(int id, int n) { asm volatile("bar.arrive %0, %1;" ::"r"(id), "r"(n) : "memory"); }
__device__ __forceinline__ void mbar_init(uint32_t a, uint32_t cnt) { asm volatile("mbarrier.init.shared::cta.b64 [%0], %1;" ::"r"(a), "r"(cnt) : "memory"); }
__device__ __forceinline__ void mbar_expect_tx(uint32_t a, uint32_t bytes) { asm volatile("mbarrier.arrive.expect_tx.shared::cta.b64 _, [%0], %1;" ::"r"(a), "r"(bytes) : "memory"); }
__device__ __forceinline__ bool mbar_try(uint32_t a, uint32_t parity) {
    uint32_t ok;
    asm volatile("{.reg .pred p; mbarrier.try_wait.parity.shared::cta.b64 p, [%1], %2; selp.u32 %0, 1, 0, p;}" : "=r"(ok) : "r"(a), "r"(parity) : "memory");
    return ok;
}
__device__ __forceinline__ void mbar_wait(uint32_t a, uint32_t parity) {
    asm volatile("{.reg .pred p, q; .reg .u32 g; mov.u32 g, 0;\n"
                 "L: mbarrier.try_wait.parity.shared::cta.b64 p, [%0], %1;\n"
                 "add.u32 g, g, 1; setp.lt.and.u32 q, g, 0x400000, !p; @q bra L;}" ::"r"(a), "r"(parity) : "memory");
}
__device__ __forceinline__ bool mbar_test(uint32_t a, uint32_t parity) {
    uint32_t ok;
    asm volatile("{.reg .pred p; mbarrier.test_wait.parity.shared::cta.b64 p, [%1], %2; selp.u32 %0, 1, 0, p;}" : "=r"(ok) : "r"(a), "r"(parity) : "memory");
    return ok;
}
__device__ __forceinline__ bool elect() {
    uint32_t ok;
    asm volatile("{.reg .pred p; elect.sync _|p, 0xffffffff; selp.u32 %0, 1, 0, p;}" : "=r"(ok));
    return ok;
}
__device__ __forceinline__ void tma_x(const CUtensorMap* tm, int slot, int q, int xq, int yq) {
    const uint32_t bar = S_BAR + 8 * slot;
    mbar_expect_tx(bar, XSTG / 4);
    asm volatile("cp.async.bulk.tensor.3d.shared::cluster.global.mbarrier::complete_tx::bytes [%0], [%1, {%3, %4, %5}], [%2];"
                 ::"r"(S_X + slot * XSTG + q * (XSTG / 4)), "l"(tm), "r"(bar), "r"(0), "r"(xq), "r"(yq) : "memory");
}
__device__ __forceinline__ void bulk_load(uint32_t dst, const void* src, uint32_t bytes, uint32_t bar) {
    asm volatile("cp.async.bulk.shared::cluster.global.mbarrier::complete_tx::bytes [%0], [%1], %2, [%3];"
                 ::"r"(dst), "l"(src), "r"(bytes), "r"(bar) : "memory");
}
__device__ __forceinline__ uint32_t lds32(uint32_t a) { uint32_t v; asm volatile("ld.shared.b32 %0, [%1];" : "=r"(v) : "r"(a)); return v; }
__device__ __forceinline__ void lds128(uint32_t* r, uint32_t a) { asm volatile("ld.shared.v4.b32 {%0,%1,%2,%3}, [%4];" : "=r"(r[0]), "=r"(r[1]), "=r"(r[2]), "=r"(r[3]) : "r"(a)); }
__device__ __forceinline__ void sts32(uint32_t a, uint32_t v) { asm volatile("st.shared.b32 [%0], %1;" ::"r"(a), "r"(v)); }
__device__ __forceinline__ void sts128(uint32_t a, uint32_t x, uint32_t y, uint32_t z, uint32_t w) { asm volatile("st.shared.v4.b32 [%0], {%1,%2,%3,%4};" ::"r"(a), "r"(x), "r"(y), "r"(z), "r"(w)); }
__device__ __forceinline__ void ldsm4(uint32_t* r, uint32_t a) {
    asm volatile("ldmatrix.sync.aligned.m8n8.x4.shared.b16 {%0,%1,%2,%3}, [%4];" : "=r"(r[0]), "=r"(r[1]), "=r"(r[2]), "=r"(r[3]) : "r"(a));
}
__device__ __forceinline__ void ldsm4s(uint32_t& r0, uint32_t& r1, uint32_t& r2, uint32_t& r3, uint32_t a) {
    asm volatile("ldmatrix.sync.aligned.m8n8.x4.shared.b16 {%0,%1,%2,%3}, [%4];" : "=r"(r0), "=r"(r1), "=r"(r2), "=r"(r3) : "r"(a));
}
__device__ __forceinline__ void ldsm2s(uint32_t& r0, uint32_t& r1, uint32_t a) {
    asm volatile("ldmatrix.sync.aligned.m8n8.x2.shared.b16 {%0,%1}, [%2];" : "=r"(r0), "=r"(r1) : "r"(a));
}
__device__ __forceinline__ void stsm4(uint32_t a, const uint32_t* r) {
    asm volatile("stmatrix.sync.aligned.m8n8.x4.shared.b16 [%4], {%0,%1,%2,%3};" ::"r"(r[0]), "r"(r[1]), "r"(r[2]), "r"(r[3]), "r"(a));
}
__device__ __forceinline__ void ldg128(uint32_t* r, const void* p) {
    asm volatile("ld.global.nc.L1::no_allocate.v4.b32 {%0,%1,%2,%3}, [%4];" : "=r"(r[0]), "=r"(r[1]), "=r"(r[2]), "=r"(r[3]) : "l"(p));
}
__device__ __forceinline__ void stg128(void* p, uint32_t x, uint32_t y, uint32_t z, uint32_t w) {
    asm volatile("st.global.L1::no_allocate.v4.b32 [%0], {%1,%2,%3,%4};" ::"l"(p), "r"(x), "r"(y), "r"(z), "r"(w));
}
__device__ __forceinline__ uint32_t bfma(uint32_t a, uint32_t b, uint32_t c) { uint32_t d; asm("fma.rn.bf16x2 %0, %1, %2, %3;" : "=r"(d) : "r"(a), "r"(b), "r"(c)); return d; }
__device__ __forceinline__ uint32_t bmul(uint32_t a, uint32_t b) { uint32_t d; asm("mul.rn.bf16x2 %0, %1, %2;" : "=r"(d) : "r"(a), "r"(b)); return d; }
__device__ __forceinline__ uint32_t vfma(uint32_t a, uint32_t b, uint32_t c) { uint32_t d; asm volatile("fma.rn.bf16x2 %0, %1, %2, %3;" : "=r"(d) : "r"(a), "r"(b), "r"(c)); return d; }
__device__ __forceinline__ void vacc(uint32_t& d, uint32_t a, uint32_t b) { asm volatile("fma.rn.bf16x2 %0, %1, %2, %0;" : "+r"(d) : "r"(a), "r"(b)); }
__device__ __forceinline__ uint32_t vadd(uint32_t a, uint32_t b) { uint32_t d; asm volatile("add.rn.bf16x2 %0, %1, %2;" : "=r"(d) : "r"(a), "r"(b)); return d; }
__device__ __forceinline__ uint32_t vsub(uint32_t a, uint32_t b) { uint32_t d; asm volatile("sub.rn.bf16x2 %0, %1, %2;" : "=r"(d) : "r"(a), "r"(b)); return d; }
__device__ __forceinline__ uint32_t vmul(uint32_t a, uint32_t b) { uint32_t d; asm volatile("mul.rn.bf16x2 %0, %1, %2;" : "=r"(d) : "r"(a), "r"(b)); return d; }
__device__ __forceinline__ uint32_t badd(uint32_t a, uint32_t b) { uint32_t d; asm("add.rn.bf16x2 %0, %1, %2;" : "=r"(d) : "r"(a), "r"(b)); return d; }
__device__ __forceinline__ uint32_t habsmax(uint32_t a, uint32_t b) { uint32_t d; asm("max.xorsign.abs.bf16x2 %0, %1, %2;" : "=r"(d) : "r"(a), "r"(b)); return d; }
__device__ __forceinline__ float bf_lo2(uint32_t v) { return __uint_as_float(v << 16); }
__device__ __forceinline__ float bf_lo(uint32_t v) { uint32_t d; asm("prmt.b32 %0, %1, 0, 0x1044;" : "=r"(d) : "r"(v)); return __uint_as_float(d); }
__device__ __forceinline__ float bf_hi(uint32_t v) { return __uint_as_float(v & 0xffff0000u); }
__device__ __forceinline__ uint32_t pack_h2(float lo, float hi) { uint32_t d; asm("cvt.rn.f16x2.f32 %0, %1, %2;" : "=r"(d) : "f"(hi), "f"(lo)); return d; }
__device__ __forceinline__ uint32_t pack_h2z(float lo, float hi) { uint32_t d; asm("cvt.rz.f16x2.f32 %0, %1, %2;" : "=r"(d) : "f"(hi), "f"(lo)); return d; }
__device__ __forceinline__ uint32_t pack_b2(float lo, float hi) { uint32_t d; asm("cvt.rn.bf16x2.f32 %0, %1, %2;" : "=r"(d) : "f"(hi), "f"(lo)); return d; }

template <int N> __device__ __forceinline__ void gelu(uint32_t* h) {
#pragma unroll
    for (int i = 0; i < N; i++) {
        uint32_t p, u, t;
        asm("fma.rn.f16x2 %0, %1, %1, %2;" : "=r"(p) : "r"(h[i]), "r"(GK2));
        asm("mul.rn.f16x2 %0, %1, %2;" : "=r"(u) : "r"(h[i]), "r"(p));
        asm("tanh.approx.f16x2 %0, %1;" : "=r"(t) : "r"(u));
        asm("fma.rn.f16x2 %0, %1, %2, %1;" : "=r"(h[i]) : "r"(h[i]), "r"(t));
    }
    pin<N>(h);
}
#define NUP 2
template <int N> __device__ __forceinline__ void gelu_a(uint32_t* t, const uint32_t* h) {
#pragma unroll
    for (int i = 0; i < N; i++) {
        uint32_t p, u;
        asm("fma.rn.f16x2 %0, %1, %1, %2;" : "=r"(p) : "r"(h[i]), "r"(GK2));
        asm("mul.rn.f16x2 %0, %1, %2;" : "=r"(u) : "r"(h[i]), "r"(p));
        if (i < N - NUP) {
            uint32_t a, b;
            asm("{.reg .b16 l, h, x; mov.b32 {l, h}, %2; tanh.approx.f16 x, l; cvt.u32.u16 %0, x; tanh.approx.f16 x, h; cvt.u32.u16 %1, x;}" : "=r"(a), "=r"(b) : "r"(u));
            asm volatile("prmt.b32 %0, %1, %2, 0x5410;" : "=r"(t[i]) : "r"(a), "r"(b));
        } else asm("tanh.approx.f16x2 %0, %1;" : "=r"(t[i]) : "r"(u));
    }
    pin<N>(t);
}
template <int N> __device__ __forceinline__ void gelu_b(uint32_t* h, const uint32_t* t) {
#pragma unroll
    for (int i = 0; i < N; i++) asm volatile("fma.rn.f16x2 %0, %1, %2, %1;" : "=r"(h[i]) : "r"(h[i]), "r"(t[i]));
}
#define RESCARRY 1
#define MIDW 12
#define OV 1
#define SB2 SB1
#define SB3 SB1
#define SB1 cfence(sink);

#define PEEL0 1
#define PEEL1 1
#define EDGE1 1
#define PRO 2
#define XFIRST 3
#define XSECOND 3
#define W2BITS 3
constexpr uint32_t W2MSK = ((1u << W2BITS) - 1) * 0x10001u, W2RND = (1u << W2BITS >> 1) * 0x10001u;
#define PEELT 1
#define CSINK lane
#define CFT 1
#define CORDER 1
template <int S, int P, int ILO, int IHI>
__device__ __forceinline__ void conv_col(uint32_t x, const uint32_t* w, uint32_t (&acc)[4][S], uint32_t (&o)[S]) {
#pragma unroll
    for (int j = 4; j >= 0; j--) {
        const int q = P - j;
        if (q < 0 || q >= S) continue;
#pragma unroll
        for (int i = IHI; i >= ILO; i--) {
            uint32_t& d = (i == 4) ? o[q] : acc[i == 4 ? 0 : 3 - i][q];
            const uint32_t ww = w[2 * (i * 5 + j)];
            if (j > 0) vacc(d, x, ww);
            else if (i == 4 && CORDER == 1) { d = acc[0][q]; vacc(d, x, ww); }
            else d = (i == 0) ? vmul(x, ww) : vfma(x, ww, acc[i == 0 ? 0 : 4 - i][q]);
        }
    }
}
#define CFENCE 0x304
#define FFB 1
struct Conv {
    uint32_t w[50];
    uint32_t s[20];
    uint32_t accA[4][8], accB[4][4];
    uint32_t sink;
    uint32_t xa[2][12], xb[2][8];
};
template <int S, int P, int MODE, int WS>
__device__ __forceinline__ void tap_col(uint32_t x, const uint32_t* w, uint32_t (&d)[S], const uint32_t (&src)[S]) {
#pragma unroll
    for (int j = 4; j >= 0; j--) {
        const int q = P - j;
        if (q < 0 || q >= S) continue;
        if (j > 0 || MODE == 0) vacc(d[q], x, w[WS * j]);
        else if (MODE == 1) d[q] = vmul(x, w[0]);
        else d[q] = vfma(x, w[0], src[q]);
    }
}
template <int R, int K> __device__ __forceinline__ void conv_ld(Conv& c, uint32_t a1) {
    ldsm4s(c.xa[R][2 * K + 2], c.xb[R][2 * K], c.xa[R][2 * K + 3], c.xb[R][2 * K + 1], a1 + K * 2 * CH * 2);
}
#define CFN(n) { if ((CFENCE >> n) & 1) cfence(c.sink); }
#define ALLCOLS CA(0); CA(1); CA(2); CB(0); CA(3); CB(1); CA(4); CB(2); CA(5); CB(3); CA(6); CB(4); CA(7); CB(5); CA(8); CB(6); CA(9); CB(7); CA(10); CA(11);
template <int R, typename Fn>
__device__ __forceinline__ void conv_out(Conv& c, uint32_t sA, uint32_t sB, Fn before_store) {
    constexpr int RB_ = FFB ? R : 0;
#define CA(p) tap_col<8, p, 0, 2>(c.xa[R][p], c.w + 41, c.accA[R], c.accA[R])
#define CB(p) tap_col<4, p, 0, 2>(c.xb[R][p], c.w + 40, c.accB[RB_], c.accB[RB_])
    CA(0); CA(1); CA(2); CB(0); CA(3); CB(1); CA(4); CB(2); CA(5); CB(3); CA(6); CB(4); CA(7); CB(5);
    before_store();
    stsm4(sA, c.accA[R]);
    CA(8); CB(6); CA(9); CB(7); CA(10); CA(11);
    stsm4(sB, c.accB[RB_]);
    stsm4(sA + 4 * CPITCH, c.accA[R] + 4);
#undef CA
#undef CB
}
template <int S, int P, int R, bool OLD, bool NEW>
__device__ __forceinline__ void dcol(const uint32_t (&x)[2][S + 4], const uint32_t* w, uint32_t (&acc)[4][S]) {
    if (!OLD && !NEW) return;
    const uint32_t d = vsub(x[0][P], x[1][P]);
    if (R == 1) {
        if (OLD) tap_col<S, P, 0, 2>(d, w + 20, acc[0], acc[0]);
        if (NEW) tap_col<S, P, 2, 2>(d, w, acc[2], acc[3]);
    } else {
        if (OLD) tap_col<S, P, 0, 2>(d, w + 30, acc[1], acc[1]);
        if (NEW) tap_col<S, P, 0, 2>(d, w + 10, acc[3], acc[3]);
    }
}
template <int R, int ILO, int IHI, bool OLD, bool NEW, typename Fn>
__device__ __forceinline__ void conv_rest(Conv& c, uint32_t a1, uint32_t a2, Fn mid) {
    if (R == 1) {
        if (OLD) {
#define CA(p) tap_col<8, p, 1, 2>(c.xa[1][p], c.s + 11, c.accA[0], c.accA[0])
#define CB(p) { if (FFB) tap_col<4, p, 1, 2>(c.xb[1][p], c.s + 10, c.accB[0], c.accB[0]); }
            ALLCOLS
#undef CA
#undef CB
#pragma unroll
            for (int q = 0; q < 8; q++) { c.accA[1][q] = vadd(c.accA[3][q], c.accA[0][q]); c.accA[0][q] = vadd(c.accA[2][q], c.accA[0][q]); }
#pragma unroll
            for (int q = 0; q < 4 * FFB; q++) { c.accB[1][q] = vadd(c.accB[3][q], c.accB[0][q]); c.accB[0][q] = vadd(c.accB[2][q], c.accB[0][q]); }
            CFN(7)
        }
        if (NEW) {
#define CA(p) tap_col<8, p, 1, 2>(c.xa[1][p], c.s + 1, c.accA[3], c.accA[3])
#define CB(p) { if (FFB) tap_col<4, p, 1, 2>(c.xb[1][p], c.s, c.accB[3], c.accB[3]); }
            ALLCOLS
#undef CA
#undef CB
            CFN(8)
        }
    }
#define CA(p) dcol<8, p, R, OLD, NEW>(c.xa, c.w + 1, c.accA)
#define CB(p) { if (FFB) dcol<4, p, R, OLD, NEW>(c.xb, c.w, c.accB); }
    CA(0); CA(1); CFN(0)
    ldsm2s(c.xa[1 - R][0], c.xa[1 - R][1], a2);
    CA(2); CB(0); CA(3); CB(1); CFN(1)
    conv_ld<1 - R, 0>(c, a1);
    CA(4); CB(2); CA(5); CB(3); CFN(2)
    conv_ld<1 - R, 1>(c, a1);
    CA(6); CB(4); CA(7); CB(5); CFN(3)
    conv_ld<1 - R, 2>(c, a1);
    CA(8); CB(6); CA(9); CB(7); CFN(4)
    conv_ld<1 - R, 3>(c, a1);
    CA(10); CA(11); CFN(5)
    ldsm2s(c.xa[1 - R][10], c.xa[1 - R][11], a2 + 10 * CH * 2);
    mid();
    CFN(9)
#undef CA
#undef CB
    if (!FFB) {
        uint32_t oB[4];
#define CB(p) conv_col<4, p, ILO, IHI>(c.xb[R][p], c.w, c.accB, oB)
        CB(0); CB(1); CB(2); CB(3); CB(4); CB(5); CB(6); CB(7);
#undef CB
        CFN(10)
    }
}

__device__ __forceinline__ uint64_t mkd(uint64_t db, uint32_t lo) { uint64_t d; asm volatile("add.u64 %0, %1, %2;" : "=l"(d) : "l"(db), "l"((uint64_t)lo)); return d; }
template <int J, int K0, int K1> __device__ __forceinline__ void gemm1(uint32_t* H, const uint32_t* a1, uint64_t db) {
#pragma unroll
    for (int kk = K0; kk < K1; kk++) {
        const uint64_t d = mkd(db, D1 + ((2 * kk * 48 + J * (CN / 8)) * 128 >> 4));
        if (kk == 0) wg_n96_h<0>(H + J * 24, a1, d);
        else wg_n96_h<1>(H + J * 24, a1 + 4 * kk, d);
    }
}
template <int K0, int K1> __device__ __forceinline__ void gemm2(uint32_t* acc, const uint32_t* H, uint64_t db) {
#pragma unroll
    for (int ks = K0; ks < K1; ks++) {
        const uint64_t d = mkd(db, D2 + (2 * ks * 12 * 128 >> 4));
        if (ks == 0) wg_n96_h<0>(acc, H, d);
        else wg_n96_h<1>(acc, H + 4 * ks, d);
    }
}

__device__ __forceinline__ float quad_sum(uint32_t v) {
    float s = bf_lo(v) + bf_hi(v);
    s += __shfl_xor_sync(0xffffffffu, s, 1);
    s += __shfl_xor_sync(0xffffffffu, s, 2);
    return s;
}
template <int r> __device__ __forceinline__ void ln_part(const uint32_t* a, uint32_t* sq) {
    uint32_t s[6], q[2];
#pragma unroll
    for (int i = 0; i < 6; i++) s[i] = badd(a[4 * i + r], a[4 * i + 2 + r]);
    sq[r] = badd(badd(badd(s[0], s[1]), badd(s[2], s[3])), badd(s[4], s[5]));
#pragma unroll
    for (int i = 0; i < 12; i++) q[i & 1] = (i < 2) ? bmul(a[2 * i + r], a[2 * i + r]) : bfma(a[2 * i + r], a[2 * i + r], q[i & 1]);
    sq[2 + r] = badd(q[0], q[1]);
    pin<1>(sq + r); pin<1>(sq + 2 + r);
}
__device__ __forceinline__ void ln_mma(float* d, const uint32_t* sq, uint64_t db) {
    asm volatile("wgmma.mma_async.sync.aligned.m64n8k16.f32.bf16.bf16 {%0,%1,%2,%3}, {%4,%5,%6,%7}, %8, 0, 1, 1, 1;"
                 : "=f"(d[0]), "=f"(d[1]), "=f"(d[2]), "=f"(d[3]) : "r"(sq[0]), "r"(sq[1]), "r"(sq[2]), "r"(sq[3]), "l"(mkd(db, D3)));
}
__device__ __forceinline__ uint32_t ln_pack(float v, float m) {
    float rs;
    asm("rsqrt.approx.ftz.f32 %0, %1;" : "=f"(rs) : "f"(v));
    rs *= LN_OUT;
    return pack_b2(rs, m * rs);
}
__device__ __forceinline__ bool ln_fin(float* d, uint32_t* st) {
    asm volatile("" : "+f"(d[0]), "+f"(d[1]), "+f"(d[2]), "+f"(d[3])::"memory");
    bool risky = false;
#pragma unroll
    for (int r = 0; r < 2; r++) {
        const float m = d[2 * r] * (-1.f / CH);
        const float t = fmaf(d[2 * r + 1], 1.f / CH, LN_EPS);
        const float v = fmaf(-m, m, t);
        risky |= !(v + v >= t);
        st[r] = ln_pack(v, m);
        d[2 * r] = m;
    }
    pin<2>(st);
    return __any_sync(0xffffffffu, risky);
}
__device__ __forceinline__ void ln_fix(uint32_t* a, const float* d, uint32_t* st) {
#pragma unroll
    for (int r = 0; r < 2; r++) {
        const uint32_t m2 = pack_b2(d[2 * r], d[2 * r]);
        uint32_t q[2];
#pragma unroll
        for (int i = 0; i < 12; i++) {
            a[2 * i + r] = badd(a[2 * i + r], m2);
            q[i & 1] = (i < 2) ? bmul(a[2 * i + r], a[2 * i + r]) : bfma(a[2 * i + r], a[2 * i + r], q[i & 1]);
        }
        st[r] = ln_pack(fmaf(quad_sum(badd(q[0], q[1])), 1.f / CH, LN_EPS), 0.f);
    }
}
template <int I0, int I1> __device__ __forceinline__ void ln_out(uint32_t* a, const uint32_t* b, const uint32_t* st) {
#pragma unroll
    for (int i = I0; i < I1; i++) {
        uint32_t v;
        asm("{.reg .b16 l, h; .reg .b32 ll, hh; mov.b32 {l, h}, %2; mov.b32 ll, {l, l}; mov.b32 hh, {h, h}; fma.rn.bf16x2 %0, %1, ll, hh;}"
            : "=r"(v) : "r"(b[i]), "r"(st[i & 1]));
        a[i] = v + 7u * (v & 0x7fff7fffu);
        pin<1>(a + i);
    }
}

__device__ __forceinline__ void epi_cvt(uint32_t* e, const uint32_t* acc) {
#pragma unroll
    for (int i = 0; i < 24; i++) {
        const uint32_t hv = acc[i];
        const float2 f = __half22float2(*reinterpret_cast<const __half2*>(&hv));
        e[i] = pack_b2(f.x, f.y);
    }
    pin<24>(e);
}
template <int R> __device__ __forceinline__ void epi_out(const uint32_t* e, const uint32_t* res, uint32_t osc2, uint8_t* gp, bool on) {
#pragma unroll
    for (int i = 0; i < 3; i++) {
        uint32_t o[4];
#pragma unroll
        for (int jj = 0; jj < 4; jj++) o[jj] = vfma(e[2 * (4 * i + jj) + R], osc2, res[(R * 3 + i) * 4 + jj]);
        asm volatile("{.reg .pred p; setp.ne.u32 p, %5, 0; @p st.global.L1::no_allocate.v4.b32 [%0], {%1,%2,%3,%4};}"
                     ::"l"(gp + R * 8 * CH * 2 + i * 64), "r"(o[0]), "r"(o[1]), "r"(o[2]), "r"(o[3]), "r"((uint32_t)(on && (!(HINT & 8) || osc2 == 0))));
    }
}
template <int R> __device__ __forceinline__ void load_res(uint32_t* res, const uint8_t* xg) {
#pragma unroll
    for (int i = 0; i < 3; i++) ldg128(res + (R * 3 + i) * 4, xg + R * 8 * CH * 2 + i * 64);
}

#define TLREC(role, idx)
#define TLRECG(role, idx)

constexpr int TSTEP = 2 * NWG * IMG_W * CH * 2;

__global__ void __launch_bounds__(384, 1)
replk_kernel(const __grid_constant__ CUtensorMap tmx, const uint8_t* __restrict__ x, const uint8_t* __restrict__ dwl,
             const uint8_t* __restrict__ dws, const uint8_t* __restrict__ w1, const uint8_t* __restrict__ w2,
             uint8_t* __restrict__ out, const uint64_t db) {
    extern __shared__ __align__(1024) uint8_t smem[];
#define ROT 2
    const int tid = (threadIdx.x + ROT * 128) % 384, lane = tid & 31;
    const int warp = __shfl_sync(0xffffffffu, tid >> 5, 0);
    const int w0 = (blockIdx.x % (IMG_W / SW)) * SW, y0 = (blockIdx.x / (IMG_W / SW)) * RB;
    if (warp < 8) { TLREC(warp >> 2, 0); TLRECG(warp >> 2, 78); }

    if (warp >= 8) {
        const int cw = warp - 8;
        if (cw == 0 && elect()) {
            if ((uint32_t)__cvta_generic_to_shared(smem) != SB) __trap();
#pragma unroll
            for (int s = 0; s < NS; s++) mbar_init(S_BAR + 8 * s, 4);
            mbar_init(S_WBAR + 40, 1);
            asm volatile("fence.mbarrier_init.release.cluster;" ::: "memory");
            TLREC(3, 43);
            mbar_expect_tx(S_WBAR + 40, 34 * CH * 2);
            bulk_load(S_C, dws, 25 * CH * 2, S_WBAR + 40);
            bulk_load(S_C + 25 * CH * 2, dwl, 9 * CH * 2, S_WBAR + 40);
            TLREC(3, 44);
        }
        bar_sync(BAR_CV, 128);
        const int xq = w0 - 2 + (cw & 1) * 18, yq = y0 - 2 + (cw >> 1);
        if (elect()) {
#pragma unroll
            for (int s = 0; s < XFIRST; s++) tma_x(&tmx, s, cw, xq, yq + 2 * s);
        }
        TLREC(3, 45);
        if (PRO & 1) bar_arrive(0, 160);
        Conv c;
        {
            const uint32_t wsA = S_C + ((cw < 3) ? lane : 32 + (lane & 15)) * 4;
            const uint32_t wsB = S_C + ((cw < 2) ? lane : 32 + (lane & 15)) * 4;
            TLREC(3, 47);
            mbar_wait(S_WBAR + 40, 0);
            TLREC(3, 40);
            uint32_t t[52];
#pragma unroll
            for (int i = 0; i < 5; i++)
#pragma unroll
                for (int j = 0; j < 5; j++) {
                    uint32_t wa = lds32(wsA + (i * 5 + j) * CH * 2), wb = lds32(wsB + (i * 5 + j) * CH * 2);
                    if (i >= 1 && i <= 3 && j >= 1 && j <= 3) {
                        wa = badd(wa, lds32(wsA + (25 + (i - 1) * 3 + j - 1) * CH * 2));
                        wb = badd(wb, lds32(wsB + (25 + (i - 1) * 3 + j - 1) * CH * 2));
                    }
                    t[2 * (i * 5 + j)] = bmul(wb, WSC2);
                    t[2 * (i * 5 + j) + 1] = bmul(wa, WSC2);
                }
            t[50] = t[51] = 0;
            if (elect()) {
#pragma unroll
                for (int s = XFIRST; s < XSECOND; s++) tma_x(&tmx, s, cw, xq, yq + 2 * s);
            }
            bar_sync(BAR_CV, 128);
            const uint32_t sc = S_C + (tid - 256) * 16;
#pragma unroll
            for (int k = 0; k < 5; k++) {
                uint32_t u[4];
#pragma unroll
                for (int i = 0; i < 4; i++) { const int n = 4 * k + i + (4 * k + i >= 10 ? 10 : 0); u[i] = badd(t[n], t[n + 10]); }
                sts128(sc + k * 2048, u[0], u[1], u[2], u[3]);
            }
#pragma unroll
            for (int k = 0; k < 5; k++) lds128(c.s + 4 * k, sc + k * 2048);
#pragma unroll
            for (int k = 0; k < 13; k++) sts128(sc + k * 2048, t[4 * k], t[4 * k + 1], t[4 * k + 2], t[4 * k + 3]);
#pragma unroll
            for (int k = 0; k < 12; k++) lds128(c.w + 4 * k, sc + k * 2048);
            asm volatile("ld.shared.v2.b32 {%0,%1}, [%2];" : "=r"(c.w[48]), "=r"(c.w[49]) : "r"(sc + 12 * 2048));
            bar_sync(BAR_CV, 128);
        }
        const int mi = lane >> 3, qd = lane & 7;
        const int chA = (cw < 3) ? qd : 8 + (qd & 3), pxA = (cw < 3) ? 8 * cw : 16 * (qd >> 2);
        const int chB = (cw < 2) ? qd : 8 + (qd & 3), pxB = (cw < 2) ? 24 + 4 * cw : 16 * (qd >> 2) + 8 + 4 * (cw - 2);
        const uint32_t a1 = S_X + ((mi & 1) ? (pxB + (mi >> 1)) * (CH * 2) + chB * 16 : (pxA + 2 + (mi >> 1)) * (CH * 2) + chA * 16);
        const uint32_t a2 = S_X + (pxA + (mi & 1)) * (CH * 2) + chA * 16;
        const uint32_t sA = S_C + (pxA >> 4) * CGRP + ((pxA & 15) + mi) * CPITCH + chA * 16;
        const uint32_t sB = S_C + (pxB >> 4) * CGRP + ((pxB & 15) + mi) * CPITCH + chB * 16;
        auto nop = [] {};
        c.sink = CSINK;
        TLREC(3, 1);
        mbar_wait(S_BAR, 0);
        ldsm2s(c.xa[0][0], c.xa[0][1], a2);
        conv_ld<0, 0>(c, a1); conv_ld<0, 1>(c, a1); conv_ld<0, 2>(c, a1); conv_ld<0, 3>(c, a1);
        ldsm2s(c.xa[0][10], c.xa[0][11], a2 + 10 * CH * 2);
        TLREC(3, 41);
        conv_rest<0, 0, 0, false, false>(c, a1 + XROW, a2 + XROW, nop);
        if (elect()) {
#pragma unroll
            for (int s = XSECOND; s < 4; s++) tma_x(&tmx, s, cw, xq, yq + 2 * s);
        }
        mbar_wait(S_BAR + 8, 0);
        TLREC(3, 42);
        conv_rest<1, 0, 1, false, true>(c, a1 + XSTG, a2 + XSTG, nop);
        conv_rest<0, 0, 2, false, true>(c, a1 + XSTG + XROW, a2 + XSTG + XROW, nop);
        TLREC(3, 2);
        bar_sync(BAR_CV, 128);
        if (elect()) tma_x(&tmx, 0, cw, xq, yq + 8);
        mbar_wait(S_BAR + 16, 0);
        TLREC(3, 3);
        int t;
        asm volatile("mov.u32 %0, 0;" : "=r"(t));
        uint32_t p1 = a1 + 2 * XSTG, p2 = a2 + 2 * XSTG, qA = sA, qB = sB;
        int dq = CBUF;
#pragma unroll 1
        for (;;) {
            const uint32_t nb = S_BAR + 8 * ((t + 3) & (NS - 1)), np = ((t + 3) / NS) & 1;
            bool ok;
            conv_rest<1, 0, 3, true, true>(c, p1, p2, nop);
            conv_out<0>(c, qA, qB, [&] {
                bar_sync(BAR_EMPTY + (t & 1), 256);
                if (elect()) tma_x(&tmx, (t + 5) & (NS - 1), cw, xq, t + 5 < NSTG ? yq + 2 * (t + 5) : -8);
            });
            CFN(6)
            conv_rest<0, 0, 3, true, true>(c, p1 + XROW, p2 + XROW, [&] { ok = mbar_test(nb, np); });
            conv_out<1>(c, qA + 2 * CGRP, qB + 2 * CGRP, nop);
            bar_arrive(BAR_FULL + (t & 1), 256);
            TLREC(3, 4 + t);
            const int dp = (t & (NS - 1)) == 1 ? -(NS - 1) * XSTG : XSTG;
            p1 += dp; p2 += dp; qA += dq; qB += dq; dq = -dq;
            t++;
            if (__all_sync(0xffffffffu, ok) && t < NT - 1) continue;
            mbar_wait(nb, np);
            if (t == NT - 1) break;
        }
        conv_rest<1, 2, 3, true, false>(c, p1, p2, nop);
        conv_out<0>(c, qA, qB, [&] { bar_sync(BAR_EMPTY + 1, 256); });
        conv_rest<0, 3, 3, true, false>(c, p1 + XROW, p2 + XROW, nop);
        conv_out<1>(c, qA + 2 * CGRP, qB + 2 * CGRP, nop);
        bar_arrive(BAR_FULL + 1, 256);
        bar_arrive(BAR_EMPTY, 256);
        bar_arrive(BAR_EMPTY + 1, 256);
        mbar_wait(S_BAR + 8 * 2, 0);
        mbar_wait(S_BAR + 8 * 3, 0);
        if (CFT == 1 && c.sink == 0x12345) sts32(S_RED + 36, c.sink);
        TLREC(3, 35);
    } else {
        const int wg = warp >> 2, wq = warp & 3;
        if (warp == 0) {
            if (PRO & 1) bar_sync(0, 160);
            if (elect()) {
#pragma unroll
                for (int s = 0; s < 5; s++) mbar_init(S_WBAR + 8 * s, 1);
                asm volatile("fence.mbarrier_init.release.cluster;" ::: "memory");
#define LW1(i) { mbar_expect_tx(S_WBAR + 8 * i, WBYTES / 3); bulk_load(S_W1 + i * (WBYTES / 3), w1 + i * (WBYTES / 3), WBYTES / 3, S_WBAR + 8 * i); }
#define LW2(i) { mbar_expect_tx(S_WBAR + 24 + 8 * i, WBYTES / 2); bulk_load(S_W2 + i * (WBYTES / 2), w2 + i * (WBYTES / 2), WBYTES / 2, S_WBAR + 24 + 8 * i); }
                LW2(0) LW2(1)
                if (!(PRO & 2)) { LW1(0) LW1(1) LW1(2) }
                TLREC(3, 46);
            }
        }
        bar_arrive(BAR_EMPTY + wg, 256);
        if (tid < 64) sts32(S_ST + tid * 4, tid < 32 ? 0x00003f80u : 0x3f800000u);
        bar_sync(BAR_W, 256);
        uint32_t osc2;
        {
            uint32_t r[18][4], m = 0;
#pragma unroll
            for (int h = 0; h < 2; h++) {
                mbar_wait(S_WBAR + 24 + 8 * h, 0);
                if (wg == 1) TLREC(3, 51 + h);
                if ((PRO & 2) && h == 0 && warp == 0 && elect()) { LW1(0) LW1(1) LW1(2) }
#pragma unroll
                for (int j = 0; j < 9; j++) {
                    uint32_t* q = r[h * 9 + j];
                    lds128(q, S_W2 + h * (WBYTES / 2) + (warp * 3 + j / 3) * 1536 + (lane >> 2) * 192 + (j % 3) * 64 + (lane & 3) * 16);
                    m = habsmax(habsmax(m, q[0]), habsmax(habsmax(q[1], q[2]), q[3]));
                }
            }
            m &= 0x7fff7fffu;
            m = __reduce_max_sync(0xffffffffu, max(m >> 16, m & 0xffffu));
            if (lane == 0) sts32(S_RED + warp * 4, m);
            bar_sync(BAR_W, 256);
            m = __reduce_max_sync(0xffffffffu, lds32(S_RED + (lane & 7) * 4));
            const int e = max(min(123 - (int)(m >> 7), 100), -15);
            const float wsc = __uint_as_float((uint32_t)(127 + e) << 23) * INV2A;
            osc2 = ((uint32_t)(127 - e + (EPI == 1 ? 112 : 0)) << 7) * 0x10001u;
#pragma unroll
            for (int j = 0; j < 18; j++)
#pragma unroll
                for (int k = 0; k < 4; k++)
                    sts32(S_W2 + (j / 9) * (WBYTES / 2) + (warp * 3 + j % 9 / 3) * 1536 + ((j % 3) * 4 + k) * 128 + lane * 4,
                          (pack_h2z(bf_lo2(r[j][k]) * wsc, bf_hi(r[j][k]) * wsc) + W2RND) & ~W2MSK);
        }
        if (wg == 1) TLREC(3, 53);
        {
            const int kr = lane & 7, nb = (kr + wg * 4 + (lane >> 3)) & 7;
#pragma unroll 1
            for (int i = 0; i < 3; i++) {
                const uint32_t base = S_W1 + (i * 4 + wq) * 6144;
                uint32_t r[6][4];
                mbar_wait(S_WBAR + 8 * i, 0);
                if (wg == 0) TLREC(3, 48 + i);
#pragma unroll
                for (int j = 0; j < 6; j++) lds128(r[j], base + kr * 768 + (j * 8 + nb) * 16);
                bar_sync(BAR_PAIR + wq, 64);
#pragma unroll
                for (int j = 0; j < 6; j++)
                    sts128(base + kr * 16 + (j * 8 + nb) * 128,
                           pack_h2(bf_lo2(r[j][0]), bf_hi(r[j][0])), pack_h2(bf_lo2(r[j][1]), bf_hi(r[j][1])),
                           pack_h2(bf_lo2(r[j][2]), bf_hi(r[j][2])), pack_h2(bf_lo2(r[j][3]), bf_hi(r[j][3])));
            }
        }
        asm volatile("fence.proxy.async.shared::cta;" ::: "memory");
        TLREC(wg, 1);
        const uint32_t cbase = S_C + wq * CGRP + (lane & 15) * CPITCH + (lane >> 4) * 16;
        uint32_t goff = ((y0 + 2 * wg + (wq >> 1)) * IMG_W + w0 + (wq & 1) * 16 + (lane >> 2)) * (CH * 2) + (lane & 3) * 16;
        uint32_t H[96], a1[24], b[24], e[24], acc[24], res[24], st[2], sq[4], t[16], sink = lane;
        float sd[4];
        bool risky;
#pragma unroll
        for (int i = 0; i < 24; i++) { acc[i] = 0; res[i] = 0; }
        const uint32_t cb = cbase + wg * CBUF;
#define LDA(dst) _Pragma("unroll") for (int kk = 0; kk < 6; kk++) ldsm4(dst + 4 * kk, cb + kk * 32);
#define FETCH() { if (!LAST) { if (PEELT || i < NT / 2 - 1) bar_sync(BAR_FULL + wg, 256); LDA(b) } }
#define RELEASE() { if (!LAST && (PEELT || i < NT / 2 - 1)) bar_arrive(BAR_EMPTY + wg, 256); }
#define FULL() { if (!LAST) bar_sync(BAR_FULL + wg, 256); }
#define LDB(k0, k1) if (!LAST) { _Pragma("unroll") for (int kk = k0; kk < k1; kk++) ldsm4(b + 4 * kk, cb + kk * 32); }
#define GL(p) gelu<8>(H + 8 * (p))
#define GA8(p) { if (!LAST) gelu_a<8>(t, H + 8 * (p)); }
#define GAF(p) gelu_a<8>(t, H + 8 * (p))
#define GB8(p) gelu_b<8>(H + 8 * (p), t)
#define G1(j, k0, k1) { if (!LAST || j != 0) gemm1<j, k0, k1>(H, a1, db); }
#define G1C(j, k0, k1) { if (!LAST || j != 0) { gemm1<j, k0, k1>(H, a1, db); C; } }
#define SX
#define LSP 8
#define LOA LO(0, LSP);
#define LOB LO(LSP, 24);
#define G2(k0, k1) gemm2<k0, k1>(acc, H, db)
#define P(ks, j, kk) G2(ks, ks + 1); G1(j, kk, kk + 1)
#define Q(j, kk, ks) G1(j, kk, kk + 1); G2(ks, ks + 1)
#define F wg_fence()
#define C wg_commit()
#define W(n) wg_wait<n>()
#define RDY(j) { if (!LAST || j != 0) pin<CN / 4>(H + (j) * (CN / 4)); }
#define CVT() epi_cvt(e, acc)
#define EO(r) epi_out<r>(e, res, osc2, out + gprev, i > 0)
#define RES(r) load_res<r>(res, x + gprev)
#define RESN(r) { if (!LAST) load_res<r>(res, x + goff); }
#define GN(w0, n) gelu<n>(H + (w0))
#define GAN(w0, n) { if (!LAST) gelu_a<n>(t, H + (w0)); }
#define GBN(w0, n) gelu_b<n>(H + (w0), t)
#define LO(i0, i1) { if (!LAST) ln_out<i0, i1>(a1, b, st); }
#define S SB1
#define SMASK 0x1fbf
#define SK(k) { if ((SMASK >> (k)) & 1) SB1 }
#define LP(r) { if (!LAST) ln_part<r>(b, sq); }
#define LMC() { if (!LAST) { ln_mma(sd, sq, db); C; } }
#define RESL() { if (LAST) { load_res<0>(res, x + goff); load_res<1>(res, x + goff); } }
#define LF() { if (!LAST) risky = ln_fin(sd, st); }
#define LX2() { if (!LAST && __builtin_expect(risky, 0)) ln_fix(b, sd, st); }
        constexpr bool LAST = false;
        bar_sync(BAR_W, 256);
        TLREC(wg, 2);
        bar_sync(BAR_FULL + wg, 256);
        LDA(b)
        bar_arrive(BAR_EMPTY + wg, 256);
        TLREC(wg, 3);
        LP(0); LP(1); F; LMC(); W(0); LF(); LX2() LO(0, 24);
        TLREC(wg, 4);
        F; G1(0, 0, 6); C; W(0); RDY(0); GAN(0, T0);
        uint32_t gprev = goff;
#pragma unroll 1
        for (int i = 0; i < NT / 2 - PEELT; i++) {
            F; G1(1,0,6); C; CVT(); EO(0); EO(1); GB8(0); GAF(1); S
            FULL() LDB(0,2)
            F; G2(0,2); C; GB8(1); GAF(2); S
            LDB(2,4)
            W(1); RDY(1); F; G2(2,4); C; GB8(2); GAF(3); S
            LDB(4,6)
            W(1); F; Q(2,0,4); Q(2,1,5); G1(2,2,6); C; GB8(3); GAF(4); S
            W(1); F; G2(6,8); C; LP(0); LP(1); GB8(4); GAF(5); S
            W(1); RDY(2); F; LMC(); G2(8,10); C; GB8(5); GAF(6); S
            W(1); F; Q(3,0,10); Q(3,1,11); G1(3,2,6); C; LF(); GB8(6); GAF(7); S
            LX2()
            W(1); F; G2(12,14); C; GB8(7); GAF(8); S
            W(1); RDY(3); F; G2(14,16); C; LO(0,24); GB8(8); GAF(9); S
            RELEASE() RESL()
            W(1); F; Q(0,0,16); Q(0,1,17); G1(0,2,6); C; RESN(0); GB8(9); GAF(10); S
            W(1); F; G2(18,20); C; RESN(1); GB8(10); GAF(11); S
            W(1); RDY(0); GB8(11); F; G2(20,24); C; S GA8(0); S
            W(0); pin<24>(acc);
            gprev = goff;
            goff += TSTEP;
            TLREC(wg, 5 + i);
        }
        {
            const int i = 1;
            constexpr bool LAST = true;
            F; G1(1,0,6); C; CVT(); EO(0); EO(1); GB8(0); GAF(1); S
            FULL() LDB(0,2)
            F; G2(0,2); C; GB8(1); GAF(2); S
            LDB(2,4)
            W(1); RDY(1); F; G2(2,4); C; GB8(2); GAF(3); S
            LDB(4,6)
            W(1); F; Q(2,0,4); Q(2,1,5); G1(2,2,6); C; GB8(3); GAF(4); S
            W(1); F; G2(6,8); C; LP(0); LP(1); GB8(4); GAF(5); S
            W(1); RDY(2); F; LMC(); G2(8,10); C; GB8(5); GAF(6); S
            W(1); F; Q(3,0,10); Q(3,1,11); G1(3,2,6); C; LF(); GB8(6); GAF(7); S
            LX2()
            W(1); F; G2(12,14); C; GB8(7); GAF(8); S
            W(1); RDY(3); F; G2(14,16); C; LO(0,24); GB8(8); GAF(9); S
            RELEASE() RESL()
            W(1); F; Q(0,0,16); Q(0,1,17); G1(0,2,6); C; RESN(0); GB8(9); GAF(10); S
            W(1); F; G2(18,20); C; RESN(1); GB8(10); GAF(11); S
            W(1); RDY(0); GB8(11); F; G2(20,24); C; S GA8(0); S
            W(0); pin<24>(acc);
            gprev = goff;
            TLREC(wg, 20);
            CVT(); EO(0); EO(1);
        }
        if (sink == 0x12345) sts32(S_RED + 36, sink);
        TLREC(wg, 77); TLRECG(wg, 79);
    }
}

typedef CUresult (*EncodeFn)(CUtensorMap*, CUtensorMapDataType, cuuint32_t, void*, const cuuint64_t*, const cuuint64_t*,
                             const cuuint32_t*, const cuuint32_t*, CUtensorMapInterleave, CUtensorMapSwizzle,
                             CUtensorMapL2promotion, CUtensorMapFloatOOBfill);

}

extern "C" void kernel_launch(void* const* d_in, const int* in_sizes, int n_in, void* d_out, int out_size) {
    static EncodeFn enc = nullptr;
    if (!enc) {
        void* fn = nullptr;
        cudaDriverEntryPointQueryResult qr;
        cudaGetDriverEntryPoint("cuTensorMapEncodeTiled", &fn, cudaEnableDefault, &qr);
        enc = (EncodeFn)fn;
        cudaFuncSetAttribute(replk_kernel, cudaFuncAttributeMaxDynamicSharedMemorySize, SMEM_BYTES);
    }
    CUtensorMap tm;
    const cuuint64_t gdim[3] = {CH, IMG_W, IMG_H};
    const cuuint64_t gstr[2] = {CH * 2, (cuuint64_t)IMG_W * CH * 2};
    const cuuint32_t box[3] = {CH, (SW + 4) / 2, 1};
    const cuuint32_t estr[3] = {1, 1, 1};
    enc(&tm, CU_TENSOR_MAP_DATA_TYPE_BFLOAT16, 3, d_in[0], gdim, gstr, box, estr, CU_TENSOR_MAP_INTERLEAVE_NONE,
        CU_TENSOR_MAP_SWIZZLE_NONE, CU_TENSOR_MAP_L2_PROMOTION_L2_256B, CU_TENSOR_MAP_FLOAT_OOB_FILL_NONE);
    replk_kernel<<<(IMG_W / SW) * (IMG_H / RB), 384, SMEM_BYTES>>>(
        tm, (const uint8_t*)d_in[0], (const uint8_t*)d_in[1], (const uint8_t*)d_in[2], (const uint8_t*)d_in[3],
        (const uint8_t*)d_in[4], (uint8_t*)d_out, (uint64_t)(128 >> 4) << 32);
}
```

```cpp
#include <cuda_runtime.h>
#include <cuda_bf16.h>
#include <cuda_fp16.h>
#include <cuda.h>
#include <stdint.h>

namespace {

constexpr int IMG_H = 512, IMG_W = 512, CH = 96, HID = 384;
constexpr int SW = 32;
constexpr int RB = 64;
constexpr int NT = RB / 2;
constexpr int NSTG = NT + 2;
constexpr int NS = 4;
constexpr int NB = 2;
#define REG_CONS 168
#define REG_CONV 168
#define CN 96
#define T0 8
#define EPI 2
#define LNCVT 0

constexpr int XROW = (SW + 4) * CH * 2;
constexpr int XSTG = 2 * XROW;
constexpr int CPITCH = 208;
constexpr int CGRP = 16 * CPITCH + 64;
constexpr int CBUF = 4 * CGRP;
constexpr int WBYTES = CH * HID * 2;
constexpr uint32_t SB = 1024;
constexpr uint32_t S_W1 = SB;
constexpr uint32_t S_W2 = S_W1 + WBYTES;
constexpr uint32_t S_X = S_W2 + WBYTES;
constexpr uint32_t S_C = S_X + NS * XSTG;
constexpr uint32_t S_BAR = S_C + NB * CBUF;
constexpr uint32_t S_WBAR = S_BAR + 8 * NS;
constexpr uint32_t S_RED = S_WBAR + 8 * 6;
constexpr uint32_t S_ST = (S_RED + 64 + 127) / 128 * 128;
constexpr int SMEM_BYTES = S_ST + 256 + 64 - SB;
static_assert(SMEM_BYTES <= 232448, "smem");

constexpr int NWG = 2;
constexpr int BAR_FULL = 1, BAR_EMPTY = 4, BAR_W = 6, BAR_RED = 7, BAR_CV = 8, BAR_PAIR = 9;

constexpr float GA = 0.3292034911525734f;
constexpr uint32_t GK2 = 0x40d940d9u;
constexpr float INV2A = 1.5188174288475842f;
constexpr uint32_t WSC2 = (uint32_t)(127 - 48) * 0x00800080u;
constexpr float LN_EPS = 1e-5f * 0x1p-96f;
constexpr float LN_OUT = GA * 0x1p-112f;

constexpr uint32_t D1 = (S_W1 >> 4) | ((48 * 128 >> 4) << 16);
constexpr uint32_t D3 = (S_ST >> 4) | ((128 >> 4) << 16);
constexpr uint32_t D2 = (S_W2 >> 4) | ((12 * 128 >> 4) << 16);

template <int SCALE_D> __device__ __forceinline__ void wg_n64_h(uint32_t* d, const uint32_t* a, uint64_t desc);
template <>
__device__ __forceinline__ void wg_n64_h<0>(uint32_t* d, const uint32_t* a, uint64_t desc) {
    asm volatile("wgmma.mma_async.sync.aligned.m64n64k16.f16.f16.f16 {"
        "%0,%1,%2,%3,%4,%5,%6,%7,%8,%9,%10,%11,%12,%13,%14,%15},"
        "{%16,%17,%18,%19}, %20, 0, 1, 1, 1;"
        : "=r"(d[0]), "=r"(d[1]), "=r"(d[2]), "=r"(d[3]), "=r"(d[4]), "=r"(d[5]), "=r"(d[6]), "=r"(d[7]),
          "=r"(d[8]), "=r"(d[9]), "=r"(d[10]), "=r"(d[11]), "=r"(d[12]), "=r"(d[13]), "=r"(d[14]), "=r"(d[15])
        : "r"(a[0]), "r"(a[1]), "r"(a[2]), "r"(a[3]), "l"(desc));
}
template <>
__device__ __forceinline__ void wg_n64_h<1>(uint32_t* d, const uint32_t* a, uint64_t desc) {
    asm volatile("wgmma.mma_async.sync.aligned.m64n64k16.f16.f16.f16 {"
        "%0,%1,%2,%3,%4,%5,%6,%7,%8,%9,%10,%11,%12,%13,%14,%15},"
        "{%16,%17,%18,%19}, %20, 1, 1, 1, 1;"
        : "+r"(d[0]), "+r"(d[1]), "+r"(d[2]), "+r"(d[3]), "+r"(d[4]), "+r"(d[5]), "+r"(d[6]), "+r"(d[7]),
          "+r"(d[8]), "+r"(d[9]), "+r"(d[10]), "+r"(d[11]), "+r"(d[12]), "+r"(d[13]), "+r"(d[14]), "+r"(d[15])
        : "r"(a[0]), "r"(a[1]), "r"(a[2]), "r"(a[3]), "l"(desc));
}
template <int SCALE_D> __device__ __forceinline__ void wg_n96_h(uint32_t* d, const uint32_t* a, uint64_t desc);
template <>
__device__ __forceinline__ void wg_n96_h<0>(uint32_t* d, const uint32_t* a, uint64_t desc) {
    asm volatile("wgmma.mma_async.sync.aligned.m64n96k16.f16.f16.f16 {"
        "%0,%1,%2,%3,%4,%5,%6,%7,%8,%9,%10,%11,%12,%13,%14,%15,"
        "%16,%17,%18,%19,%20,%21,%22,%23},"
        "{%24,%25,%26,%27}, %28, 0, 1, 1, 1;"
        : "=r"(d[0]), "=r"(d[1]), "=r"(d[2]), "=r"(d[3]), "=r"(d[4]), "=r"(d[5]), "=r"(d[6]), "=r"(d[7]),
          "=r"(d[8]), "=r"(d[9]), "=r"(d[10]), "=r"(d[11]), "=r"(d[12]), "=r"(d[13]), "=r"(d[14]), "=r"(d[15]),
          "=r"(d[16]), "=r"(d[17]), "=r"(d[18]), "=r"(d[19]), "=r"(d[20]), "=r"(d[21]), "=r"(d[22]), "=r"(d[23])
        : "r"(a[0]), "r"(a[1]), "r"(a[2]), "r"(a[3]), "l"(desc));
}
template <>
__device__ __forceinline__ void wg_n96_h<1>(uint32_t* d, const uint32_t* a, uint64_t desc) {
    asm volatile("wgmma.mma_async.sync.aligned.m64n96k16.f16.f16.f16 {"
        "%0,%1,%2,%3,%4,%5,%6,%7,%8,%9,%10,%11,%12,%13,%14,%15,"
        "%16,%17,%18,%19,%20,%21,%22,%23},"
        "{%24,%25,%26,%27}, %28, 1, 1, 1, 1;"
        : "+r"(d[0]), "+r"(d[1]), "+r"(d[2]), "+r"(d[3]), "+r"(d[4]), "+r"(d[5]), "+r"(d[6]), "+r"(d[7]),
          "+r"(d[8]), "+r"(d[9]), "+r"(d[10]), "+r"(d[11]), "+r"(d[12]), "+r"(d[13]), "+r"(d[14]), "+r"(d[15]),
          "+r"(d[16]), "+r"(d[17]), "+r"(d[18]), "+r"(d[19]), "+r"(d[20]), "+r"(d[21]), "+r"(d[22]), "+r"(d[23])
        : "r"(a[0]), "r"(a[1]), "r"(a[2]), "r"(a[3]), "l"(desc));
}
template <int SCALE_D> __device__ __forceinline__ void wg_n128_h(uint32_t* d, const uint32_t* a, uint64_t desc);
template <>
__device__ __forceinline__ void wg_n128_h<0>(uint32_t* d, const uint32_t* a, uint64_t desc) {
    asm volatile("wgmma.mma_async.sync.aligned.m64n128k16.f16.f16.f16 {"
        "%0,%1,%2,%3,%4,%5,%6,%7,%8,%9,%10,%11,%12,%13,%14,%15,"
        "%16,%17,%18,%19,%20,%21,%22,%23,%24,%25,%26,%27,%28,%29,%30,%31},"
        "{%32,%33,%34,%35}, %36, 0, 1, 1, 1;"
        : "=r"(d[0]), "=r"(d[1]), "=r"(d[2]), "=r"(d[3]), "=r"(d[4]), "=r"(d[5]), "=r"(d[6]), "=r"(d[7]),
          "=r"(d[8]), "=r"(d[9]), "=r"(d[10]), "=r"(d[11]), "=r"(d[12]), "=r"(d[13]), "=r"(d[14]), "=r"(d[15]),
          "=r"(d[16]), "=r"(d[17]), "=r"(d[18]), "=r"(d[19]), "=r"(d[20]), "=r"(d[21]), "=r"(d[22]), "=r"(d[23]),
          "=r"(d[24]), "=r"(d[25]), "=r"(d[26]), "=r"(d[27]), "=r"(d[28]), "=r"(d[29]), "=r"(d[30]), "=r"(d[31])
        : "r"(a[0]), "r"(a[1]), "r"(a[2]), "r"(a[3]), "l"(desc));
}
template <>
__device__ __forceinline__ void wg_n128_h<1>(uint32_t* d, const uint32_t* a, uint64_t desc) {
    asm volatile("wgmma.mma_async.sync.aligned.m64n128k16.f16.f16.f16 {"
        "%0,%1,%2,%3,%4,%5,%6,%7,%8,%9,%10,%11,%12,%13,%14,%15,"
        "%16,%17,%18,%19,%20,%21,%22,%23,%24,%25,%26,%27,%28,%29,%30,%31},"
        "{%32,%33,%34,%35}, %36, 1, 1, 1, 1;"
        : "+r"(d[0]), "+r"(d[1]), "+r"(d[2]), "+r"(d[3]), "+r"(d[4]), "+r"(d[5]), "+r"(d[6]), "+r"(d[7]),
          "+r"(d[8]), "+r"(d[9]), "+r"(d[10]), "+r"(d[11]), "+r"(d[12]), "+r"(d[13]), "+r"(d[14]), "+r"(d[15]),
          "+r"(d[16]), "+r"(d[17]), "+r"(d[18]), "+r"(d[19]), "+r"(d[20]), "+r"(d[21]), "+r"(d[22]), "+r"(d[23]),
          "+r"(d[24]), "+r"(d[25]), "+r"(d[26]), "+r"(d[27]), "+r"(d[28]), "+r"(d[29]), "+r"(d[30]), "+r"(d[31])
        : "r"(a[0]), "r"(a[1]), "r"(a[2]), "r"(a[3]), "l"(desc));
}
template <int SCALE_D> __device__ __forceinline__ void wg_n192_h(uint32_t* d, const uint32_t* a, uint64_t desc);
template <>
__device__ __forceinline__ void wg_n192_h<0>(uint32_t* d, const uint32_t* a, uint64_t desc) {
    asm volatile("wgmma.mma_async.sync.aligned.m64n192k16.f16.f16.f16 {"
        "%0,%1,%2,%3,%4,%5,%6,%7,%8,%9,%10,%11,%12,%13,%14,%15,"
        "%16,%17,%18,%19,%20,%21,%22,%23,%24,%25,%26,%27,%28,%29,%30,%31,"
        "%32,%33,%34,%35,%36,%37,%38,%39,%40,%41,%42,%43,%44,%45,%46,%47},"
        "{%48,%49,%50,%51}, %52, 0, 1, 1, 1;"
        : "=r"(d[0]), "=r"(d[1]), "=r"(d[2]), "=r"(d[3]), "=r"(d[4]), "=r"(d[5]), "=r"(d[6]), "=r"(d[7]),
          "=r"(d[8]), "=r"(d[9]), "=r"(d[10]), "=r"(d[11]), "=r"(d[12]), "=r"(d[13]), "=r"(d[14]), "=r"(d[15]),
          "=r"(d[16]), "=r"(d[17]), "=r"(d[18]), "=r"(d[19]), "=r"(d[20]), "=r"(d[21]), "=r"(d[22]), "=r"(d[23]),
          "=r"(d[24]), "=r"(d[25]), "=r"(d[26]), "=r"(d[27]), "=r"(d[28]), "=r"(d[29]), "=r"(d[30]), "=r"(d[31]),
          "=r"(d[32]), "=r"(d[33]), "=r"(d[34]), "=r"(d[35]), "=r"(d[36]), "=r"(d[37]), "=r"(d[38]), "=r"(d[39]),
          "=r"(d[40]), "=r"(d[41]), "=r"(d[42]), "=r"(d[43]), "=r"(d[44]), "=r"(d[45]), "=r"(d[46]), "=r"(d[47])
        : "r"(a[0]), "r"(a[1]), "r"(a[2]), "r"(a[3]), "l"(desc));
}
template <>
__device__ __forceinline__ void wg_n192_h<1>(uint32_t* d, const uint32_t* a, uint64_t desc) {
    asm volatile("wgmma.mma_async.sync.aligned.m64n192k16.f16.f16.f16 {"
        "%0,%1,%2,%3,%4,%5,%6,%7,%8,%9,%10,%11,%12,%13,%14,%15,"
        "%16,%17,%18,%19,%20,%21,%22,%23,%24,%25,%26,%27,%28,%29,%30,%31,"
        "%32,%33,%34,%35,%36,%37,%38,%39,%40,%41,%42,%43,%44,%45,%46,%47},"
        "{%48,%49,%50,%51}, %52, 1, 1, 1, 1;"
        : "+r"(d[0]), "+r"(d[1]), "+r"(d[2]), "+r"(d[3]), "+r"(d[4]), "+r"(d[5]), "+r"(d[6]), "+r"(d[7]),
          "+r"(d[8]), "+r"(d[9]), "+r"(d[10]), "+r"(d[11]), "+r"(d[12]), "+r"(d[13]), "+r"(d[14]), "+r"(d[15]),
          "+r"(d[16]), "+r"(d[17]), "+r"(d[18]), "+r"(d[19]), "+r"(d[20]), "+r"(d[21]), "+r"(d[22]), "+r"(d[23]),
          "+r"(d[24]), "+r"(d[25]), "+r"(d[26]), "+r"(d[27]), "+r"(d[28]), "+r"(d[29]), "+r"(d[30]), "+r"(d[31]),
          "+r"(d[32]), "+r"(d[33]), "+r"(d[34]), "+r"(d[35]), "+r"(d[36]), "+r"(d[37]), "+r"(d[38]), "+r"(d[39]),
          "+r"(d[40]), "+r"(d[41]), "+r"(d[42]), "+r"(d[43]), "+r"(d[44]), "+r"(d[45]), "+r"(d[46]), "+r"(d[47])
        : "r"(a[0]), "r"(a[1]), "r"(a[2]), "r"(a[3]), "l"(desc));
}

#define HINT 0
constexpr uint64_t POL_EF = 0x12F0000000000000ull;
__device__ __forceinline__ void wg_fence() { asm volatile("wgmma.fence.sync.aligned;" ::: "memory"); }
__device__ __forceinline__ void wg_commit() { asm volatile("wgmma.commit_group.sync.aligned;" ::: "memory"); }
template <int N> __device__ __forceinline__ void wg_wait() { asm volatile("wgmma.wait_group.sync.aligned %0;" ::"n"(N) : "memory"); }
template <int N> __device__ __forceinline__ void pin(uint32_t* r) {
#pragma unroll
    for (int i = 0; i < N; i++) asm volatile("" : "+r"(r[i])::"memory");
}
__device__ __forceinline__ void sbar() { asm volatile("griddepcontrol.launch_dependents;" ::: "memory"); }

#define CK64 0
__device__ __forceinline__ void cfence(uint32_t& sink) {
    uint32_t ck;
    asm volatile("mov.u32 %0, %%clock;" : "=r"(ck)::"memory");
    sink ^= ck;
}
#define SFT 0
__device__ __forceinline__ void bar_sync(int id, int n) { asm volatile("bar.sync %0, %1;" ::"r"(id), "r"(n) : "memory"); }
__device__ __forceinline__ void bar_arrive(int id, int n) { asm volatile("bar.arrive %0, %1;" ::"r"(id), "r"(n) : "memory"); }
#define BARP 1
template <int ID> __device__ __forceinline__ void bar_sync_wg(int wg) {
    if (BARP & 1) asm volatile("{.reg .pred p; setp.ne.u32 p, %0, 0; @p bar.sync %2, 256; @!p bar.sync %1, 256;}" ::"r"(wg), "n"(ID), "n"(ID + 1) : "memory");
    else bar_sync(ID + wg, 256);
}
template <int ID> __device__ __forceinline__ void bar_arrive_wg(int wg) {
    if (BARP & 2) asm volatile("{.reg .pred p; setp.ne.u32 p, %0, 0; @p bar.arrive %2, 256; @!p bar.arrive %1, 256;}" ::"r"(wg), "n"(ID), "n"(ID + 1) : "memory");
    else bar_arrive(ID + wg, 256);
}
__device__ __forceinline__ void mbar_init(uint32_t a, uint32_t cnt) { asm volatile("mbarrier.init.shared::cta.b64 [%0], %1;" ::"r"(a), "r"(cnt) : "memory"); }
__device__ __forceinline__ void mbar_expect_tx(uint32_t a, uint32_t bytes) { asm volatile("mbarrier.arrive.expect_tx.shared::cta.b64 _, [%0], %1;" ::"r"(a), "r"(bytes) : "memory"); }
__device__ __forceinline__ bool mbar_try(uint32_t a, uint32_t parity) {
    uint32_t ok;
    asm volatile("{.reg .pred p; mbarrier.try_wait.parity.shared::cta.b64 p, [%1], %2; selp.u32 %0, 1, 0, p;}" : "=r"(ok) : "r"(a), "r"(parity) : "memory");
    return ok;
}
__device__ __forceinline__ void mbar_wait(uint32_t a, uint32_t parity) {
    asm volatile("{.reg .pred p, q; .reg .u32 g; mov.u32 g, 0;\n"
                 "L: mbarrier.try_wait.parity.shared::cta.b64 p, [%0], %1;\n"
                 "add.u32 g, g, 1; setp.lt.and.u32 q, g, 0x400000, !p; @q bra L;}" ::"r"(a), "r"(parity) : "memory");
}
__device__ __forceinline__ bool mbar_test(uint32_t a, uint32_t parity) {
    uint32_t ok;
    asm volatile("{.reg .pred p; mbarrier.test_wait.parity.shared::cta.b64 p, [%1], %2; selp.u32 %0, 1, 0, p;}" : "=r"(ok) : "r"(a), "r"(parity) : "memory");
    return ok;
}
__device__ __forceinline__ bool elect() {
    uint32_t ok;
    asm volatile("{.reg .pred p; elect.sync _|p, 0xffffffff; selp.u32 %0, 1, 0, p;}" : "=r"(ok));
    return ok;
}
__device__ __forceinline__ void tma_x(const CUtensorMap* tm, int slot, int q, int xq, int yq) {
    const uint32_t bar = S_BAR + 8 * slot;
    mbar_expect_tx(bar, XSTG / 4);
    asm volatile("cp.async.bulk.tensor.3d.shared::cluster.global.mbarrier::complete_tx::bytes [%0], [%1, {%3, %4, %5}], [%2];"
                 ::"r"(S_X + slot * XSTG + q * (XSTG / 4)), "l"(tm), "r"(bar), "r"(0), "r"(xq), "r"(yq) : "memory");
}
__device__ __forceinline__ void bulk_load(uint32_t dst, const void* src, uint32_t bytes, uint32_t bar) {
    asm volatile("cp.async.bulk.shared::cluster.global.mbarrier::complete_tx::bytes [%0], [%1], %2, [%3];"
                 ::"r"(dst), "l"(src), "r"(bytes), "r"(bar) : "memory");
}
__device__ __forceinline__ uint32_t lds32(uint32_t a) { uint32_t v; asm volatile("ld.shared.b32 %0, [%1];" : "=r"(v) : "r"(a)); return v; }
__device__ __forceinline__ void lds128(uint32_t* r, uint32_t a) { asm volatile("ld.shared.v4.b32 {%0,%1,%2,%3}, [%4];" : "=r"(r[0]), "=r"(r[1]), "=r"(r[2]), "=r"(r[3]) : "r"(a)); }
__device__ __forceinline__ void sts32(uint32_t a, uint32_t v) { asm volatile("st.shared.b32 [%0], %1;" ::"r"(a), "r"(v)); }
__device__ __forceinline__ void sts128(uint32_t a, uint32_t x, uint32_t y, uint32_t z, uint32_t w) { asm volatile("st.shared.v4.b32 [%0], {%1,%2,%3,%4};" ::"r"(a), "r"(x), "r"(y), "r"(z), "r"(w)); }
__device__ __forceinline__ void ldsm4(uint32_t* r, uint32_t a) {
    asm volatile("ldmatrix.sync.aligned.m8n8.x4.shared.b16 {%0,%1,%2,%3}, [%4];" : "=r"(r[0]), "=r"(r[1]), "=r"(r[2]), "=r"(r[3]) : "r"(a));
}
__device__ __forceinline__ void ldsm4s(uint32_t& r0, uint32_t& r1, uint32_t& r2, uint32_t& r3, uint32_t a) {
    asm volatile("ldmatrix.sync.aligned.m8n8.x4.shared.b16 {%0,%1,%2,%3}, [%4];" : "=r"(r0), "=r"(r1), "=r"(r2), "=r"(r3) : "r"(a));
}
__device__ __forceinline__ void ldsm2s(uint32_t& r0, uint32_t& r1, uint32_t a) {
    asm volatile("ldmatrix.sync.aligned.m8n8.x2.shared.b16 {%0,%1}, [%2];" : "=r"(r0), "=r"(r1) : "r"(a));
}
__device__ __forceinline__ void stsm4(uint32_t a, const uint32_t* r) {
    asm volatile("stmatrix.sync.aligned.m8n8.x4.shared.b16 [%4], {%0,%1,%2,%3};" ::"r"(r[0]), "r"(r[1]), "r"(r[2]), "r"(r[3]), "r"(a));
}
__device__ __forceinline__ void ldg128(uint32_t* r, const void* p) {
    asm volatile("ld.global.nc.L1::no_allocate.v4.b32 {%0,%1,%2,%3}, [%4];" : "=r"(r[0]), "=r"(r[1]), "=r"(r[2]), "=r"(r[3]) : "l"(p));
}
__device__ __forceinline__ void stg128(void* p, uint32_t x, uint32_t y, uint32_t z, uint32_t w) {
    asm volatile("st.global.L1::no_allocate.v4.b32 [%0], {%1,%2,%3,%4};" ::"l"(p), "r"(x), "r"(y), "r"(z), "r"(w));
}
__device__ __forceinline__ uint32_t bfma(uint32_t a, uint32_t b, uint32_t c) { uint32_t d; asm("fma.rn.bf16x2 %0, %1, %2, %3;" : "=r"(d) : "r"(a), "r"(b), "r"(c)); return d; }
__device__ __forceinline__ uint32_t bmul(uint32_t a, uint32_t b) { uint32_t d; asm("mul.rn.bf16x2 %0, %1, %2;" : "=r"(d) : "r"(a), "r"(b)); return d; }
__device__ __forceinline__ uint32_t vfma(uint32_t a, uint32_t b, uint32_t c) { uint32_t d; asm volatile("fma.rn.bf16x2 %0, %1, %2, %3;" : "=r"(d) : "r"(a), "r"(b), "r"(c)); return d; }
__device__ __forceinline__ void vacc(uint32_t& d, uint32_t a, uint32_t b) { asm volatile("fma.rn.bf16x2 %0, %1, %2, %0;" : "+r"(d) : "r"(a), "r"(b)); }
__device__ __forceinline__ uint32_t vadd(uint32_t a, uint32_t b) { uint32_t d; asm volatile("add.rn.bf16x2 %0, %1, %2;" : "=r"(d) : "r"(a), "r"(b)); return d; }
__device__ __forceinline__ uint32_t vsub(uint32_t a, uint32_t b) { uint32_t d; asm volatile("sub.rn.bf16x2 %0, %1, %2;" : "=r"(d) : "r"(a), "r"(b)); return d; }
__device__ __forceinline__ uint32_t vmul(uint32_t a, uint32_t b) { uint32_t d; asm volatile("mul.rn.bf16x2 %0, %1, %2;" : "=r"(d) : "r"(a), "r"(b)); return d; }
__device__ __forceinline__ uint32_t badd(uint32_t a, uint32_t b) { uint32_t d; asm("add.rn.bf16x2 %0, %1, %2;" : "=r"(d) : "r"(a), "r"(b)); return d; }
__device__ __forceinline__ uint32_t habsmax(uint32_t a, uint32_t b) { uint32_t d; asm("max.xorsign.abs.bf16x2 %0, %1, %2;" : "=r"(d) : "r"(a), "r"(b)); return d; }
__device__ __forceinline__ float bf_lo2(uint32_t v) { return __uint_as_float(v << 16); }
__device__ __forceinline__ float bf_lo(uint32_t v) { uint32_t d; asm("prmt.b32 %0, %1, 0, 0x1044;" : "=r"(d) : "r"(v)); return __uint_as_float(d); }
__device__ __forceinline__ float bf_hi(uint32_t v) { return __uint_as_float(v & 0xffff0000u); }
__device__ __forceinline__ uint32_t pack_h2(float lo, float hi) { uint32_t d; asm("cvt.rn.f16x2.f32 %0, %1, %2;" : "=r"(d) : "f"(hi), "f"(lo)); return d; }
__device__ __forceinline__ uint32_t pack_h2z(float lo, float hi) { uint32_t d; asm("cvt.rz.f16x2.f32 %0, %1, %2;" : "=r"(d) : "f"(hi), "f"(lo)); return d; }
__device__ __forceinline__ uint32_t b2h(uint32_t v) { return v + 7u * (v & 0x7fff7fffu); }
__device__ __forceinline__ uint32_t pack_b2(float lo, float hi) { uint32_t d; asm("cvt.rn.bf16x2.f32 %0, %1, %2;" : "=r"(d) : "f"(hi), "f"(lo)); return d; }

template <int N> __device__ __forceinline__ void gelu(uint32_t* h) {
#pragma unroll
    for (int i = 0; i < N; i++) {
        uint32_t p, u, t;
        asm("fma.rn.f16x2 %0, %1, %1, %2;" : "=r"(p) : "r"(h[i]), "r"(GK2));
        asm("mul.rn.f16x2 %0, %1, %2;" : "=r"(u) : "r"(h[i]), "r"(p));
        asm("tanh.approx.f16x2 %0, %1;" : "=r"(t) : "r"(u));
        asm("fma.rn.f16x2 %0, %1, %2, %1;" : "=r"(h[i]) : "r"(h[i]), "r"(t));
    }
    pin<N>(h);
}
#define NUP 2
template <int N> __device__ __forceinline__ void gelu_a(uint32_t* t, const uint32_t* h) {
#pragma unroll
    for (int i = 0; i < N; i++) {
        uint32_t p, u;
        asm("fma.rn.f16x2 %0, %1, %1, %2;" : "=r"(p) : "r"(h[i]), "r"(GK2));
        asm("mul.rn.f16x2 %0, %1, %2;" : "=r"(u) : "r"(h[i]), "r"(p));
        if (i < N - NUP) {
            uint32_t a, b;
            asm("{.reg .b16 l, h, x; mov.b32 {l, h}, %2; tanh.approx.f16 x, l; cvt.u32.u16 %0, x; tanh.approx.f16 x, h; cvt.u32.u16 %1, x;}" : "=r"(a), "=r"(b) : "r"(u));
            asm volatile("prmt.b32 %0, %1, %2, 0x5410;" : "=r"(t[i]) : "r"(a), "r"(b));
        } else asm("tanh.approx.f16x2 %0, %1;" : "=r"(t[i]) : "r"(u));
    }
    pin<N>(t);
}
template <int N> __device__ __forceinline__ void gelu_b(uint32_t* h, const uint32_t* t) {
#pragma unroll
    for (int i = 0; i < N; i++) asm volatile("fma.rn.f16x2 %0, %1, %2, %1;" : "=r"(h[i]) : "r"(h[i]), "r"(t[i]));
}
#define RESCARRY 1
#define MIDW 12
#define OV 1
#define SB2 SB1
#define SB3 SB1
#define SB1 cfence(sink);

#define PEEL0 1
#define PEEL1 1
#define EDGE1 1
#define PRO 2
#define XFIRST 2
#define XSECOND 3
#define W2BITS 3
constexpr uint32_t W2MSK = ((1u << W2BITS) - 1) * 0x10001u, W2RND = (1u << W2BITS >> 1) * 0x10001u;
#define NOCNT 1
#define PAD 0
#define SWAPA 0
#define WCVT 3
#define PAIR 1
#define EARLY 1
#define TAPF 1
#define PEELT 1
#define CSINK lane
#define CFT 1
#define CORDER 1
template <int S, int P, int ILO, int IHI>
__device__ __forceinline__ void conv_col(uint32_t x, const uint32_t* w, uint32_t (&acc)[4][S], uint32_t (&o)[S]) {
#pragma unroll
    for (int j = 4; j >= 0; j--) {
        const int q = P - j;
        if (q < 0 || q >= S) continue;
#pragma unroll
        for (int i = IHI; i >= ILO; i--) {
            uint32_t& d = (i == 4) ? o[q] : acc[i == 4 ? 0 : 3 - i][q];
            const uint32_t ww = w[2 * (i * 5 + j)];
            if (j > 0) vacc(d, x, ww);
            else if (i == 4 && CORDER == 1) { d = acc[0][q]; vacc(d, x, ww); }
            else d = (i == 0) ? vmul(x, ww) : vfma(x, ww, acc[i == 0 ? 0 : 4 - i][q]);
        }
    }
}
#define CFENCE 0x304
#define FFB 1
struct Conv {
    uint32_t w[50];
    uint32_t s[20];
    uint32_t accA[4][8], accB[4][4];
    uint32_t sink;
    uint32_t xa[2][12], xb[2][8];
};
template <int S, int P, int MODE, int WS>
__device__ __forceinline__ void tap_col(uint32_t x, const uint32_t* w, uint32_t (&d)[S], const uint32_t (&src)[S]) {
#pragma unroll
    for (int j = 4; j >= 0; j--) {
        const int q = P - j;
        if (q < 0 || q >= S) continue;
        if (j > 0 || MODE == 0) vacc(d[q], x, w[WS * j]);
        else if (MODE == 1) d[q] = vmul(x, w[0]);
        else d[q] = vfma(x, w[0], src[q]);
    }
}
template <int R, int K> __device__ __forceinline__ void conv_ld(Conv& c, uint32_t a1) {
    ldsm4s(c.xa[R][2 * K + 2], c.xb[R][2 * K], c.xa[R][2 * K + 3], c.xb[R][2 * K + 1], a1 + K * 2 * CH * 2);
}
#define CFN(n) { if ((CFENCE >> n) & 1) cfence(c.sink); }
#define ALLCOLS CA(0); CA(1); CA(2); CB(0); CA(3); CB(1); CA(4); CB(2); CA(5); CB(3); CA(6); CB(4); CA(7); CB(5); CA(8); CB(6); CA(9); CB(7); CA(10); CA(11);
template <int R, typename Fn>
__device__ __forceinline__ void conv_out(Conv& c, uint32_t sA, uint32_t sB, Fn before_store) {
    constexpr int RB_ = FFB ? R : 0;
#define CA(p) tap_col<8, p, 0, 2>(c.xa[R][p], c.w + 41, c.accA[R], c.accA[R])
#define CB(p) tap_col<4, p, 0, 2>(c.xb[R][p], c.w + 40, c.accB[RB_], c.accB[RB_])
    CA(0); CA(1); CA(2); CB(0); CA(3); CB(1); CA(4); CB(2); CA(5); CB(3); CA(6); CB(4); CA(7); CB(5);
    before_store();
    stsm4(sA, c.accA[R]);
    CA(8); CB(6); CA(9); CB(7); CA(10); CA(11);
    stsm4(sB, c.accB[RB_]);
    stsm4(sA + 4 * CPITCH, c.accA[R] + 4);
#undef CA
#undef CB
}
template <int S, int P, int R, bool OLD, bool NEW>
__device__ __forceinline__ void dcol(const uint32_t (&x)[2][S + 4], const uint32_t* w, uint32_t (&acc)[4][S]) {
    if (!OLD && !NEW) return;
    const uint32_t d = vsub(x[0][P], x[1][P]);
    if (R == 1) {
        if (OLD) tap_col<S, P, 0, 2>(d, w + 20, acc[0], acc[0]);
        if (NEW) tap_col<S, P, 2, 2>(d, w, acc[2], acc[3]);
    } else {
        if (OLD) tap_col<S, P, 0, 2>(d, w + 30, acc[1], acc[1]);
        if (NEW) tap_col<S, P, 0, 2>(d, w + 10, acc[3], acc[3]);
    }
}
template <int R, int ILO, int IHI, bool OLD, bool NEW, typename Fn>
__device__ __forceinline__ void conv_rest(Conv& c, uint32_t a1, uint32_t a2, Fn mid) {
    if (R == 1) {
        if (OLD) {
#define CA(p) tap_col<8, p, 1, 2>(c.xa[1][p], c.s + 11, c.accA[0], c.accA[0])
#define CB(p) { if (FFB) tap_col<4, p, 1, 2>(c.xb[1][p], c.s + 10, c.accB[0], c.accB[0]); }
            ALLCOLS
#undef CA
#undef CB
#pragma unroll
            for (int q = 0; q < 8; q++) { c.accA[1][q] = vadd(c.accA[3][q], c.accA[0][q]); c.accA[0][q] = vadd(c.accA[2][q], c.accA[0][q]); }
#pragma unroll
            for (int q = 0; q < 4 * FFB; q++) { c.accB[1][q] = vadd(c.accB[3][q], c.accB[0][q]); c.accB[0][q] = vadd(c.accB[2][q], c.accB[0][q]); }
            CFN(7)
        }
        if (NEW) {
#define CA(p) tap_col<8, p, 1, 2>(c.xa[1][p], c.s + 1, c.accA[3], c.accA[3])
#define CB(p) { if (FFB) tap_col<4, p, 1, 2>(c.xb[1][p], c.s, c.accB[3], c.accB[3]); }
            ALLCOLS
#undef CA
#undef CB
            CFN(8)
        }
    }
#define CA(p) dcol<8, p, R, OLD, NEW>(c.xa, c.w + 1, c.accA)
#define CB(p) { if (FFB) dcol<4, p, R, OLD, NEW>(c.xb, c.w, c.accB); }
    CA(0); CA(1); CFN(0)
    ldsm2s(c.xa[1 - R][0], c.xa[1 - R][1], a2);
    CA(2); CB(0); CA(3); CB(1); CFN(1)
    conv_ld<1 - R, 0>(c, a1);
    CA(4); CB(2); CA(5); CB(3); CFN(2)
    conv_ld<1 - R, 1>(c, a1);
    CA(6); CB(4); CA(7); CB(5); CFN(3)
    conv_ld<1 - R, 2>(c, a1);
    CA(8); CB(6); CA(9); CB(7); CFN(4)
    conv_ld<1 - R, 3>(c, a1);
    CA(10); CA(11); CFN(5)
    ldsm2s(c.xa[1 - R][10], c.xa[1 - R][11], a2 + 10 * CH * 2);
    mid();
    CFN(9)
#undef CA
#undef CB
    if (!FFB) {
        uint32_t oB[4];
#define CB(p) conv_col<4, p, ILO, IHI>(c.xb[R][p], c.w, c.accB, oB)
        CB(0); CB(1); CB(2); CB(3); CB(4); CB(5); CB(6); CB(7);
#undef CB
        CFN(10)
    }
}

__device__ __forceinline__ uint64_t mkd(uint64_t db, uint32_t lo) { uint64_t d; asm volatile("add.u64 %0, %1, %2;" : "=l"(d) : "l"(db), "l"((uint64_t)lo)); return d; }
template <int J, int K0, int K1> __device__ __forceinline__ void gemm1(uint32_t* H, const uint32_t* a1, uint64_t db) {
#pragma unroll
    for (int kk = K0; kk < K1; kk++) {
        const uint64_t d = mkd(db, D1 + ((2 * kk * 48 + J * (CN / 8)) * 128 >> 4));
        if (kk == 0) wg_n96_h<0>(H + J * 24, a1, d);
        else wg_n96_h<1>(H + J * 24, a1 + 4 * kk, d);
    }
}
template <int K0, int K1> __device__ __forceinline__ void gemm2(uint32_t* acc, const uint32_t* H, uint64_t db) {
#pragma unroll
    for (int ks = K0; ks < K1; ks++) {
        const uint64_t d = mkd(db, D2 + (2 * ks * 12 * 128 >> 4));
        if (ks == 0) wg_n96_h<0>(acc, H, d);
        else wg_n96_h<1>(acc, H + 4 * ks, d);
    }
}

__device__ __forceinline__ float quad_sum(uint32_t v) {
    float s = bf_lo(v) + bf_hi(v);
    s += __shfl_xor_sync(0xffffffffu, s, 1);
    s += __shfl_xor_sync(0xffffffffu, s, 2);
    return s;
}
template <int r> __device__ __forceinline__ void ln_part(const uint32_t* a, uint32_t* sq) {
    uint32_t s[6], q[2];
#pragma unroll
    for (int i = 0; i < 6; i++) s[i] = badd(a[4 * i + r], a[4 * i + 2 + r]);
    sq[r] = badd(badd(badd(s[0], s[1]), badd(s[2], s[3])), badd(s[4], s[5]));
#pragma unroll
    for (int i = 0; i < 12; i++) q[i & 1] = (i < 2) ? bmul(a[2 * i + r], a[2 * i + r]) : bfma(a[2 * i + r], a[2 * i + r], q[i & 1]);
    sq[2 + r] = badd(q[0], q[1]);
    pin<1>(sq + r); pin<1>(sq + 2 + r);
}
__device__ __forceinline__ void ln_mma(float* d, const uint32_t* sq, uint64_t db) {
    asm volatile("wgmma.mma_async.sync.aligned.m64n8k16.f32.bf16.bf16 {%0,%1,%2,%3}, {%4,%5,%6,%7}, %8, 0, 1, 1, 1;"
                 : "=f"(d[0]), "=f"(d[1]), "=f"(d[2]), "=f"(d[3]) : "r"(sq[0]), "r"(sq[1]), "r"(sq[2]), "r"(sq[3]), "l"(mkd(db, D3)));
}
__device__ __forceinline__ float rsq(float v) { float r; asm("rsqrt.approx.ftz.f32 %0, %1;" : "=f"(r) : "f"(v)); return r; }
__device__ __forceinline__ bool ln_fin(float* d, uint32_t* st) {
    asm volatile("" : "+f"(d[0]), "+f"(d[1]), "+f"(d[2]), "+f"(d[3])::"memory");
    bool risky = false;
#pragma unroll
    for (int r = 0; r < 2; r++) {
        const float q = rsq(fmaf(-d[2 * r], d[2 * r], d[2 * r + 1] + LN_EPS * (CH * CH)));
        const float z = d[2 * r] * q;
        risky |= !(fabsf(z) <= 1.f);
        st[r] = pack_b2(q * (LN_OUT * CH), z * -LN_OUT);
    }
    pin<2>(st);
    return __any_sync(0xffffffffu, risky);
}
__device__ __forceinline__ void ln_fix(uint32_t* a, const float* d, uint32_t* st) {
#pragma unroll
    for (int r = 0; r < 2; r++) {
        const uint32_t m2 = pack_b2(d[2 * r] * (-1.f / CH), d[2 * r] * (-1.f / CH));
        uint32_t q[2];
#pragma unroll
        for (int i = 0; i < 12; i++) {
            a[2 * i + r] = badd(a[2 * i + r], m2);
            q[i & 1] = (i < 2) ? bmul(a[2 * i + r], a[2 * i + r]) : bfma(a[2 * i + r], a[2 * i + r], q[i & 1]);
        }
        st[r] = pack_b2(rsq(fmaf(quad_sum(badd(q[0], q[1])), 1.f / CH, LN_EPS)) * LN_OUT, 0.f);
    }
}
template <int I0, int I1> __device__ __forceinline__ void ln_out(uint32_t* a, const uint32_t* b, const uint32_t* st) {
#pragma unroll
    for (int i = I0; i < I1; i++) {
        uint32_t v;
        asm("{.reg .b16 l, h; .reg .b32 ll, hh; mov.b32 {l, h}, %2; mov.b32 ll, {l, l}; mov.b32 hh, {h, h}; fma.rn.bf16x2 %0, %1, ll, hh;}"
            : "=r"(v) : "r"(b[i]), "r"(st[i & 1]));
        a[i] = v + 7u * (v & 0x7fff7fffu);
        pin<1>(a + i);
    }
}

__device__ __forceinline__ void epi_cvt(uint32_t* e, const uint32_t* acc) {
#pragma unroll
    for (int i = 0; i < 24; i++) {
        const uint32_t hv = acc[i];
        const float2 f = __half22float2(*reinterpret_cast<const __half2*>(&hv));
        e[i] = pack_b2(f.x, f.y);
    }
    pin<24>(e);
}
template <int R> __device__ __forceinline__ void epi_out(const uint32_t* e, const uint32_t* res, uint32_t osc2, uint8_t* gp, bool on) {
#pragma unroll
    for (int i = 0; i < 3; i++) {
        uint32_t o[4];
#pragma unroll
        for (int jj = 0; jj < 4; jj++) o[jj] = vfma(e[2 * (4 * i + jj) + R], osc2, res[(R * 3 + i) * 4 + jj]);
        asm volatile("{.reg .pred p; setp.ne.u32 p, %5, 0; @p st.global.L1::no_allocate.v4.b32 [%0], {%1,%2,%3,%4};}"
                     ::"l"(gp + R * 8 * CH * 2 + i * 64), "r"(o[0]), "r"(o[1]), "r"(o[2]), "r"(o[3]), "r"((uint32_t)(on && (!(HINT & 8) || osc2 == 0))));
    }
}
template <int R> __device__ __forceinline__ void load_res(uint32_t* res, const uint8_t* xg) {
#pragma unroll
    for (int i = 0; i < 3; i++) ldg128(res + (R * 3 + i) * 4, xg + R * 8 * CH * 2 + i * 64);
}

#define CYS(k)
#define TLREC(role, idx)
#define TLRECG(role, idx)

constexpr int TSTEP = 2 * NWG * IMG_W * CH * 2;

__global__ void __launch_bounds__(384, 1)
replk_kernel(const __grid_constant__ CUtensorMap tmx, const uint8_t* __restrict__ x, const uint8_t* __restrict__ dwl,
             const uint8_t* __restrict__ dws, const uint8_t* __restrict__ w1, const uint8_t* __restrict__ w2,
             uint8_t* __restrict__ out, const uint64_t db) {
    extern __shared__ __align__(1024) uint8_t smem[];
#define ROT 2
    const int tid = (threadIdx.x + ROT * 128) % 384, lane = tid & 31;
    const int warp = __shfl_sync(0xffffffffu, tid >> 5, 0);
    const int w0 = (blockIdx.x % (IMG_W / SW)) * SW, y0 = (blockIdx.x / (IMG_W / SW)) * RB;
    const int up = PAIR & ~(blockIdx.x / (IMG_W / SW));
    const int dy = 1 - 2 * up, yb = y0 - 2 + (RB + 3) * up;
    if (warp < 8) { TLREC(warp >> 2, 0); TLRECG(warp >> 2, 78); }
    auto first_loads = [&] {
        if ((uint32_t)__cvta_generic_to_shared(smem) != SB) __trap();
#pragma unroll
        for (int s = 0; s < NS; s++) mbar_init(S_BAR + 8 * s, 4);
        asm volatile("fence.mbarrier_init.release.cluster;" ::: "memory");
        TLREC(3, 43);
        if (EARLY) {
#pragma unroll
            for (int q = 0; q < 4; q++) tma_x(&tmx, 0, q, w0 - 2 + (q & 1) * 18, yb + dy * (q >> 1));
        }
        TLREC(3, 44);
    };

    if (warp >= 8) {
        const int cw = warp - 8;
        const int tj = min((tid - 256) / 24, 4), tc = (tid - 256) % 24;
        uint2 ts[5], tl[3];
        auto tap_loads = [&] {
#pragma unroll
            for (int i = 0; i < 5; i++) ts[i] = __ldg(reinterpret_cast<const uint2*>(dws) + ((2 + dy * (i - 2)) * 5 + tj) * 24 + tc);
#pragma unroll
            for (int i = 0; i < 3; i++) tl[i] = __ldg(reinterpret_cast<const uint2*>(dwl) + ((1 + dy * (i - 1)) * 3 + (tj + 2) % 3) * 24 + tc);
        };
        if (TAPF) tap_loads();
        if (cw == 0 && elect()) first_loads();
        bar_sync(BAR_CV, 128);
        const int xq = w0 - 2 + (cw & 1) * 18, yq = yb + dy * (cw >> 1);
        if (elect()) {
#pragma unroll
            for (int s = EARLY; s < XFIRST; s++) tma_x(&tmx, s, cw, xq, yq + 2 * dy * s);
        }
        TLREC(3, 45);
        if (!TAPF) tap_loads();
        if (PRO & 1) bar_arrive(0, 160);
        Conv c;
        {
            TLREC(3, 47);
            const uint32_t lm = (tj & 3) ? ~0u : 0u;
            uint32_t v[7][2];
#pragma unroll
            for (int i = 0; i < 5; i++) {
                v[i][0] = ts[i].x; v[i][1] = ts[i].y;
                if (i >= 1 && i <= 3) { v[i][0] = badd(v[i][0], tl[i - 1].x & lm); v[i][1] = badd(v[i][1], tl[i - 1].y & lm); }
                v[i][0] = bmul(v[i][0], WSC2); v[i][1] = bmul(v[i][1], WSC2);
            }
#pragma unroll
            for (int u = 0; u < 2; u++) { v[5][u] = badd(v[0][u], v[1][u]); v[6][u] = badd(v[2][u], v[3][u]); }
#pragma unroll
            for (int i = 0; i < 7; i++)
                asm volatile("st.shared.v2.b32 [%0], {%1, %2};" ::"r"(S_C + ((i * 5 + tj) * 24 + tc) * 8), "r"(v[i][0]), "r"(v[i][1]) : "memory");
            bar_sync(BAR_CV, 128);
            TLREC(3, 40);
            if (elect()) {
#pragma unroll
                for (int s = XFIRST; s < XSECOND; s++) tma_x(&tmx, s, cw, xq, yq + 2 * dy * s);
            }
            const int qd = lane & 7, u = (lane >> 3) & 1;
            const uint32_t ws = S_C + ((cw < 2 + u) ? qd : 8 + (qd & 3)) * 16;
#pragma unroll
            for (int k = 0; k < 12; k++) ldsm4(c.w + 4 * k, ws + ((lane >> 4) + 2 * k) * CH * 2);
            ldsm2s(c.w[48], c.w[49], ws + 24 * CH * 2);
#pragma unroll
            for (int k = 0; k < 5; k++) ldsm4(c.s + 4 * k, ws + ((lane >> 4) + 25 + 2 * k) * CH * 2);
        }
        const int mi = lane >> 3, qd = lane & 7;
        const int chA = (cw < 3) ? qd : 8 + (qd & 3), pxA = (cw < 3) ? 8 * cw : 16 * (qd >> 2);
        const int chB = (cw < 2) ? qd : 8 + (qd & 3), pxB = (cw < 2) ? 24 + 4 * cw : 16 * (qd >> 2) + 8 + 4 * (cw - 2);
        const uint32_t a1 = S_X + ((mi & 1) ? (pxB + (mi >> 1)) * (CH * 2) + chB * 16 : (pxA + 2 + (mi >> 1)) * (CH * 2) + chA * 16);
        const uint32_t a2 = S_X + (pxA + (mi & 1)) * (CH * 2) + chA * 16;
        const uint32_t sA = S_C + (pxA >> 4) * CGRP + ((pxA & 15) + mi) * CPITCH + chA * 16;
        const uint32_t sB = S_C + (pxB >> 4) * CGRP + ((pxB & 15) + mi) * CPITCH + chB * 16;
        auto nop = [] {};
        c.sink = CSINK;
        TLREC(3, 1); CYS(0)
        mbar_wait(S_BAR, 0);
        ldsm2s(c.xa[0][0], c.xa[0][1], a2);
        conv_ld<0, 0>(c, a1); conv_ld<0, 1>(c, a1); conv_ld<0, 2>(c, a1); conv_ld<0, 3>(c, a1);
        ldsm2s(c.xa[0][10], c.xa[0][11], a2 + 10 * CH * 2);
        TLREC(3, 41);
        conv_rest<0, 0, 0, false, false>(c, a1 + XROW, a2 + XROW, nop);
        if (elect()) {
#pragma unroll
            for (int s = XSECOND; s < 4; s++) tma_x(&tmx, s, cw, xq, yq + 2 * dy * s);
        }
        mbar_wait(S_BAR + 8, 0);
        TLREC(3, 42); CYS(1)
        conv_rest<1, 0, 1, false, true>(c, a1 + XSTG, a2 + XSTG, nop);
        conv_rest<0, 0, 2, false, true>(c, a1 + XSTG + XROW, a2 + XSTG + XROW, nop);
        TLREC(3, 2);
        bar_sync(BAR_CV, 128);
        if (elect()) tma_x(&tmx, 0, cw, xq, yq + 8 * dy);
        mbar_wait(S_BAR + 16, 0);
        TLREC(3, 3); CYS(2)
        int t;
        asm volatile("mov.u32 %0, 0;" : "=r"(t));
        uint32_t p1 = a1 + 2 * XSTG, p2 = a2 + 2 * XSTG, qA = sA, qB = sB;
        int dq = CBUF, yn = yq + 10 * dy;
#pragma unroll 1
        for (;;) {
            const uint32_t nb = S_BAR + 8 * ((t + 3) & (NS - 1)), np = ((t + 3) / NS) & 1;
            bool ok;
            conv_rest<1, 0, 3, true, true>(c, p1, p2, nop);
            conv_out<0>(c, qA, qB, [&] {
                bar_sync(BAR_EMPTY + (t & 1), 256);
                if (elect()) tma_x(&tmx, (t + 5) & (NS - 1), cw, xq, t + 5 < NSTG ? yn : -8);
            });
            CFN(6)
            conv_rest<0, 0, 3, true, true>(c, p1 + XROW, p2 + XROW, [&] { ok = mbar_test(nb, np); });
            conv_out<1>(c, qA + 2 * CGRP, qB + 2 * CGRP, nop);
            bar_arrive(BAR_FULL + (t & 1), 256);
            TLREC(3, 4 + t);
            const int dp = (t & (NS - 1)) == 1 ? -(NS - 1) * XSTG : XSTG;
            p1 += dp; p2 += dp; qA += dq; qB += dq; dq = -dq; yn += 2 * dy;
            t++;
            if (__all_sync(0xffffffffu, ok) && t < NT - 1) continue;
            mbar_wait(nb, np);
            if (t == NT - 1) break;
        }
        conv_rest<1, 2, 3, true, false>(c, p1, p2, nop);
        conv_out<0>(c, qA, qB, [&] { bar_sync(BAR_EMPTY + 1, 256); });
        conv_rest<0, 3, 3, true, false>(c, p1 + XROW, p2 + XROW, nop);
        conv_out<1>(c, qA + 2 * CGRP, qB + 2 * CGRP, nop);
        bar_arrive(BAR_FULL + 1, 256);
        bar_arrive(BAR_EMPTY, 256);
        bar_arrive(BAR_EMPTY + 1, 256);
        mbar_wait(S_BAR + 8 * 2, 0);
        mbar_wait(S_BAR + 8 * 3, 0);
        if (CFT == 1 && c.sink == 0x12345) sts32(S_RED + 36, c.sink);
        TLREC(3, 35); CYS(3)
    } else {
        const int wg = warp >> 2, wq = warp & 3;
        if (warp == 0) {
            if (PRO & 1) bar_sync(0, 160);
            if (elect()) {
#pragma unroll
                for (int s = 0; s < 5; s++) mbar_init(S_WBAR + 8 * s, 1);
                asm volatile("fence.mbarrier_init.release.cluster;" ::: "memory");
#define LW1(i) { mbar_expect_tx(S_WBAR + 8 * i, WBYTES / 3); bulk_load(S_W1 + i * (WBYTES / 3), w1 + i * (WBYTES / 3), WBYTES / 3, S_WBAR + 8 * i); }
#define LW2(i) { mbar_expect_tx(S_WBAR + 24 + 8 * i, WBYTES / 2); bulk_load(S_W2 + i * (WBYTES / 2), w2 + i * (WBYTES / 2), WBYTES / 2, S_WBAR + 24 + 8 * i); }
                if (PRO & 4) { LW1(0) LW1(1) LW1(2) if (!(PRO & 2)) { LW2(0) LW2(1) } }
                else { LW2(0) LW2(1) if (!(PRO & 2)) { LW1(0) LW1(1) LW1(2) } }
                TLREC(3, 46);
            }
        }
        bar_arrive(BAR_EMPTY + wg, 256);
        if (tid < 64) sts32(S_ST + tid * 4, tid < 32 ? 0x00003f80u : 0x42c00000u);
        bar_sync(BAR_W, 256);
        uint32_t osc2;
        auto cvt_w2 = [&] {
            uint32_t r[18][4], m = 0;
#pragma unroll
            for (int h = 0; h < 2; h++) {
                mbar_wait(S_WBAR + 24 + 8 * h, 0);
                if (wg == 1) TLREC(3, 51 + h);
                if ((PRO & 6) == 2 && h == 0 && warp == 0 && elect()) { LW1(0) LW1(1) LW1(2) }
#pragma unroll
                for (int j = 0; j < 9; j++) {
                    uint32_t* q = r[h * 9 + j];
                    lds128(q, S_W2 + h * (WBYTES / 2) + (warp * 3 + j / 3) * 1536 + (lane >> 2) * 192 + (j % 3) * 64 + (lane & 3) * 16);
                    m = habsmax(habsmax(m, q[0]), habsmax(habsmax(q[1], q[2]), q[3]));
                }
            }
            m &= 0x7fff7fffu;
            m = __reduce_max_sync(0xffffffffu, max(m >> 16, m & 0xffffu));
            if (lane == 0) sts32(S_RED + warp * 4, m);
            bar_sync(BAR_W, 256);
            m = __reduce_max_sync(0xffffffffu, lds32(S_RED + (lane & 7) * 4));
            const int e = max(min(123 - (int)(m >> 7), 100), -5);
            const uint32_t chi = (0x3fc2u + ((e - 112) << 7)) * 0x10001u, clo = (0x3b51u + ((e - 112) << 7)) * 0x10001u;
            const float wsc = __uint_as_float((uint32_t)(127 + e) << 23) * INV2A;
            osc2 = ((uint32_t)(127 - e + (EPI == 1 ? 112 : 0)) << 7) * 0x10001u;
#pragma unroll
            for (int j = 0; j < 18; j++) {
#pragma unroll
                for (int k = 0; k < 4; k++)
                    r[j][k] = ((WCVT >> (k & 1)) & 1) ? b2h(bfma(r[j][k], chi, bmul(r[j][k], clo)))
                                                      : (pack_h2z(bf_lo2(r[j][k]) * wsc, bf_hi(r[j][k]) * wsc) + W2RND) & ~W2MSK;
                stsm4(S_W2 + (j / 9) * (WBYTES / 2) + (warp * 3 + j % 9 / 3) * 1536 + (j % 3) * 512 + lane * 16, r[j]);
            }
        };
        auto cvt_w1 = [&] {
            const int kr = lane & 7, nb = (kr + wg * 4 + (lane >> 3)) & 7;
#pragma unroll 1
            for (int i = 0; i < 3; i++) {
                const uint32_t base = S_W1 + (i * 4 + wq) * 6144;
                uint32_t r[6][4];
                mbar_wait(S_WBAR + 8 * i, 0);
                if (wg == 0) TLREC(3, 48 + i);
                if ((PRO & 6) == 6 && i == 0 && warp == 0 && elect()) { LW2(0) LW2(1) }
#pragma unroll
                for (int j = 0; j < 6; j++) lds128(r[j], base + kr * 768 + (j * 8 + nb) * 16);
                bar_sync(BAR_PAIR + wq, 64);
#pragma unroll
                for (int j = 0; j < 6; j++)
                    sts128(base + kr * 16 + (j * 8 + nb) * 128,
                           (WCVT & 4) ? b2h(bmul(r[j][0], 0x07800780u)) : pack_h2(bf_lo2(r[j][0]), bf_hi(r[j][0])),
                           (WCVT & 8) ? b2h(bmul(r[j][1], 0x07800780u)) : pack_h2(bf_lo2(r[j][1]), bf_hi(r[j][1])),
                           (WCVT & 4) ? b2h(bmul(r[j][2], 0x07800780u)) : pack_h2(bf_lo2(r[j][2]), bf_hi(r[j][2])),
                           (WCVT & 8) ? b2h(bmul(r[j][3], 0x07800780u)) : pack_h2(bf_lo2(r[j][3]), bf_hi(r[j][3])));
            }
        };
        if (PRO & 4) { cvt_w1(); if (wg == 1) TLREC(3, 53); cvt_w2(); }
        else { cvt_w2(); if (wg == 1) TLREC(3, 53); cvt_w1(); }
        asm volatile("fence.proxy.async.shared::cta;" ::: "memory");
        TLREC(wg, 1);
        const uint32_t cbase = S_C + wq * CGRP + (lane & 15) * CPITCH + (lane >> 4) * 16;
        const int gstep = dy * TSTEP;
        uint32_t goff = ((yb + dy * (2 + 2 * wg + (wq >> 1))) * IMG_W + w0 + (wq & 1) * 16 + (lane >> 2)) * (CH * 2) + (lane & 3) * 16;
        uint32_t H[96], a1[24], b[24], e[24], acc[24], res[24], st[2], sq[4], t[16], sink = lane;
        float sd[4];
        bool risky;
#pragma unroll
        for (int i = 0; i < 24; i++) { acc[i] = 0; res[i] = 0; }
        const uint32_t cb = cbase + wg * CBUF;
#define LDA(dst) _Pragma("unroll") for (int kk = 0; kk < 6; kk++) ldsm4(dst + 4 * kk, cb + kk * 32);
#define FETCH() { if (!LAST) { if (PEELT || i < NT / 2 - 1) bar_sync(BAR_FULL + wg, 256); LDA(b) } }
#define RELEASE() { if (!LAST) bar_arrive_wg<BAR_EMPTY>(wg); }
#define FULL() { if (!LAST) bar_sync_wg<BAR_FULL>(wg); }
#define LDB(k0, k1) if (!LAST) { _Pragma("unroll") for (int kk = k0; kk < k1; kk++) ldsm4(b + 4 * kk, cb + kk * 32); }
#define GL(p) gelu<8>(H + 8 * (p))
#define GA8(p) { if (!LAST) gelu_a<8>(t, H + 8 * (p)); }
#define GAF(p) gelu_a<8>(t, H + 8 * (p))
#define GB8(p) gelu_b<8>(H + 8 * (p), t)
#define G1(j, k0, k1) { if (!LAST || j != 0) gemm1<j, k0, k1>(H, a1, db); }
#define G1C(j, k0, k1) { if (!LAST || j != 0) { gemm1<j, k0, k1>(H, a1, db); C; } }
#define SX
#define LSP 8
#define LOA LO(0, LSP);
#define LOB LO(LSP, 24);
#define G2(k0, k1) gemm2<k0, k1>(acc, H, db)
#define P(ks, j, kk) G2(ks, ks + 1); G1(j, kk, kk + 1)
#define Q(j, kk, ks) G1(j, kk, kk + 1); G2(ks, ks + 1)
#define F wg_fence()
#define C wg_commit()
#define W(n) wg_wait<n>()
#define RDY(j) { if (!LAST || j != 0) pin<CN / 4>(H + (j) * (CN / 4)); }
#define CVT() epi_cvt(e, acc)
#define EO(r) epi_out<r>(e, res, osc2, out - gstep + goff, i > 0)
#define RES(r) load_res<r>(res, x + goff - (i > 0 ? gstep : 0))
#define RESN(r) { if (!LAST) load_res<r>(res, x + goff); }
#define GN(w0, n) gelu<n>(H + (w0))
#define GAN(w0, n) { if (!LAST) gelu_a<n>(t, H + (w0)); }
#define GBN(w0, n) gelu_b<n>(H + (w0), t)
#define LO(i0, i1) { if (!LAST) ln_out<i0, i1>(a1, b, st); }
#define S SB1
#define SMASK 0x1fbf
#define SK(k) { if ((SMASK >> (k)) & 1) SB1 }
#define LP(r) { if (!LAST) ln_part<r>(b, sq); }
#define LMC() { if (!LAST) { ln_mma(sd, sq, db); C; } }
#define RESL() { if (LAST) { load_res<0>(res, x + goff); load_res<1>(res, x + goff); } }
#define LF() { if (!LAST) risky = ln_fin(sd, st); }
#define LX2() { if (!LAST && __builtin_expect(risky, 0)) ln_fix(b, sd, st); }
        constexpr bool LAST = false;
        bar_sync(BAR_W, 256);
        TLREC(wg, 2); CYS(2)
        bar_sync(BAR_FULL + wg, 256);
        LDA(b)
        bar_arrive(BAR_EMPTY + wg, 256);
        TLREC(wg, 3); CYS(3)
        {
        constexpr uint64_t db = (uint64_t)(128 >> 4) << 32;
        LP(0); LP(1); F; LMC(); W(0); LF(); LX2() LO(0, 24);
        TLREC(wg, 4);
        F; G1(0, 0, 6); C; W(0); RDY(0); GAN(0, T0);
        }
        CYS(0)
        const uint32_t g1 = (y0 + 4 + (RB - 8) * up) * IMG_W * CH * 2, gend = (y0 + RB - 4 - (RB - 8) * up) * IMG_W * CH * 2;
#pragma unroll 1
        do {
            const int i = (goff >= g1) != (up != 0);
            F; G1(1,0,1); G1(1,1,2); G1(1,2,3); G1(1,3,4); G1(1,4,5); G1(1,5,6); C; CVT(); EO(0); EO(1); GB8(0); GAF(1); S
            FULL() LDB(0,2)
            F; G2(0,1); G2(1,2); C; GB8(1); GAF(2); S
            LDB(2,4)
            W(1); RDY(1); F; G2(2,3); G2(3,4); C; GB8(2); GAF(3); S
            LDB(4,6)
            W(1); F; G1(2,0,1); G2(4,5); G1(2,1,2); G2(5,6); G1(2,2,3); G1(2,3,4); C; GB8(3); GAF(4); S
            W(1); F; G1C(2,4,6); G2(6,7); G2(7,8); C; LP(0); LP(1); GB8(4); GAF(5); S
            W(1); RDY(2); F; LMC(); G2(8,9); G2(9,10); C; GB8(5); GAF(6); S
            W(1); F; G1(3,0,1); G2(10,11); G1(3,1,2); G2(11,12); G1(3,2,3); G1(3,3,4); C; LF(); GB8(6); GAF(7); S
            LX2()
            W(1); F; G1C(3,4,6); G2(12,13); G2(13,14); C; GB8(7); GAF(8); S
            W(1); RDY(3); F; G2(14,15); G2(15,16); C; LO(0,16); GB8(8); GAF(9); S
            RELEASE() RESL()
            W(1); F; G1(0,0,1); G2(16,17); G1(0,1,2); G2(17,18); G1(0,2,3); G1(0,3,4); C; LO(16,24); GB8(9); GAF(10); S
            W(1); F; G1C(0,4,6); G2(18,19); G2(19,20); C; RESN(1); RESN(0); GB8(10); GAF(11); S
            W(1); RDY(0); GB8(11); F; G2(20,21); G2(21,22); G2(22,23); G2(23,24); C; S GA8(0); S
            W(0); pin<24>(acc);
            goff += gstep;
        } while ((goff < gend) != (up != 0));
        CYS(1)
        {
            const int i = 1;
            constexpr bool LAST = true;
            F; G1(1,0,1); G1(1,1,2); G1(1,2,3); G1(1,3,4); G1(1,4,5); G1(1,5,6); C; CVT(); EO(0); EO(1); GB8(0); GAF(1); S
            FULL() LDB(0,2)
            F; G2(0,1); G2(1,2); C; GB8(1); GAF(2); S
            LDB(2,4)
            W(1); RDY(1); F; G2(2,3); G2(3,4); C; GB8(2); GAF(3); S
            LDB(4,6)
            W(1); F; G1(2,0,1); G2(4,5); G1(2,1,2); G2(5,6); G1(2,2,3); G1(2,3,4); C; GB8(3); GAF(4); S
            W(1); F; G1C(2,4,6); G2(6,7); G2(7,8); C; LP(0); LP(1); GB8(4); GAF(5); S
            W(1); RDY(2); F; LMC(); G2(8,9); G2(9,10); C; GB8(5); GAF(6); S
            W(1); F; G1(3,0,1); G2(10,11); G1(3,1,2); G2(11,12); G1(3,2,3); G1(3,3,4); C; LF(); GB8(6); GAF(7); S
            LX2()
            W(1); F; G1C(3,4,6); G2(12,13); G2(13,14); C; GB8(7); GAF(8); S
            W(1); RDY(3); F; G2(14,15); G2(15,16); C; LO(0,16); GB8(8); GAF(9); S
            RELEASE() RESL()
            W(1); F; G1(0,0,1); G2(16,17); G1(0,1,2); G2(17,18); G1(0,2,3); G1(0,3,4); C; LO(16,24); GB8(9); GAF(10); S
            W(1); F; G1C(0,4,6); G2(18,19); G2(19,20); C; RESN(1); RESN(0); GB8(10); GAF(11); S
            W(1); RDY(0); GB8(11); F; G2(20,21); G2(21,22); G2(22,23); G2(23,24); C; S GA8(0); S
            W(0); pin<24>(acc);
            TLREC(wg, 20);
            CVT(); epi_out<0>(e, res, osc2, out + goff, true); epi_out<1>(e, res, osc2, out + goff, true);
        }
        if (sink == 0x12345) sts32(S_RED + 36, sink);
        TLREC(wg, 77); TLRECG(wg, 79);
    }
}

typedef CUresult (*EncodeFn)(CUtensorMap*, CUtensorMapDataType, cuuint32_t, void*, const cuuint64_t*, const cuuint64_t*,
                             const cuuint32_t*, const cuuint32_t*, CUtensorMapInterleave, CUtensorMapSwizzle,
                             CUtensorMapL2promotion, CUtensorMapFloatOOBfill);

}

extern "C" void kernel_launch(void* const* d_in, const int* in_sizes, int n_in, void* d_out, int out_size) {
    static EncodeFn enc = nullptr;
    if (!enc) {
        void* fn = nullptr;
        cudaDriverEntryPointQueryResult qr;
        cudaGetDriverEntryPoint("cuTensorMapEncodeTiled", &fn, cudaEnableDefault, &qr);
        enc = (EncodeFn)fn;
        cudaFuncSetAttribute(replk_kernel, cudaFuncAttributeMaxDynamicSharedMemorySize, SMEM_BYTES);
    }
    CUtensorMap tm;
    const cuuint64_t gdim[3] = {CH, IMG_W, IMG_H};
    const cuuint64_t gstr[2] = {CH * 2, (cuuint64_t)IMG_W * CH * 2};
    const cuuint32_t box[3] = {CH, (SW + 4) / 2, 1};
    const cuuint32_t estr[3] = {1, 1, 1};
    enc(&tm, CU_TENSOR_MAP_DATA_TYPE_BFLOAT16, 3, d_in[0], gdim, gstr, box, estr, CU_TENSOR_MAP_INTERLEAVE_NONE,
        CU_TENSOR_MAP_SWIZZLE_NONE, CU_TENSOR_MAP_L2_PROMOTION_L2_256B, CU_TENSOR_MAP_FLOAT_OOB_FILL_NONE);
    replk_kernel<<<(IMG_W / SW) * (IMG_H / RB), 384, SMEM_BYTES>>>(
        tm, (const uint8_t*)d_in[0], (const uint8_t*)d_in[1], (const uint8_t*)d_in[2], (const uint8_t*)d_in[3],
        (const uint8_t*)d_in[4], (uint8_t*)d_out, (uint64_t)(128 >> 4) << 32);
}
```

```cpp
#include <cuda_runtime.h>
#include <cuda_bf16.h>
#include <cuda_fp16.h>
#include <cuda.h>
#include <stdint.h>

namespace {

constexpr int IMG_H = 512, IMG_W = 512, CH = 96, HID = 384;
constexpr int SW = 32;
constexpr int RB = 64;
constexpr int NT = RB / 2;
constexpr int NSTG = NT + 2;
constexpr int NS = 4;
constexpr int NB = 2;
#define REG_CONS 168
#define REG_CONV 168
#define CN 96
#define T0 8
#define EPI 2
#define LNCVT 0

constexpr int XROW = (SW + 4) * CH * 2;
constexpr int XSTG = 2 * XROW;
constexpr int CPITCH = 208;
constexpr int CGRP = 16 * CPITCH + 64;
constexpr int CBUF = 4 * CGRP;
constexpr int WBYTES = CH * HID * 2;
constexpr uint32_t SB = 1024;
constexpr uint32_t S_W1 = SB;
constexpr uint32_t S_W2 = S_W1 + WBYTES;
constexpr uint32_t S_X = S_W2 + WBYTES;
constexpr uint32_t S_C = S_X + NS * XSTG;
constexpr uint32_t S_BAR = S_C + NB * CBUF;
constexpr uint32_t S_WBAR = S_BAR + 8 * NS;
constexpr uint32_t S_RED = S_WBAR + 8 * 6;
constexpr uint32_t S_ST = (S_RED + 64 + 127) / 128 * 128;
constexpr int SMEM_BYTES = S_ST + 256 + 64 - SB;
static_assert(SMEM_BYTES <= 232448, "smem");

constexpr int NWG = 2;
constexpr int BAR_FULL = 1, BAR_EMPTY = 4, BAR_W = 6, BAR_RED = 7, BAR_CV = 8, BAR_PAIR = 9;

constexpr float GA = 0.3292034911525734f;
constexpr uint32_t GK2 = 0x40d940d9u;
constexpr float INV2A = 1.5188174288475842f;
constexpr uint32_t WSC2 = (uint32_t)(127 - 48) * 0x00800080u;
constexpr float LN_EPS = 1e-5f * 0x1p-96f;
constexpr float LN_OUT = GA * 0x1p-112f;

constexpr uint32_t D1 = (S_W1 >> 4) | ((48 * 128 >> 4) << 16);
constexpr uint32_t D3 = (S_ST >> 4) | ((128 >> 4) << 16);
constexpr uint32_t D2 = (S_W2 >> 4) | ((12 * 128 >> 4) << 16);

template <int SCALE_D> __device__ __forceinline__ void wg_n64_h(uint32_t* d, const uint32_t* a, uint64_t desc);
template <>
__device__ __forceinline__ void wg_n64_h<0>(uint32_t* d, const uint32_t* a, uint64_t desc) {
    asm volatile("wgmma.mma_async.sync.aligned.m64n64k16.f16.f16.f16 {"
        "%0,%1,%2,%3,%4,%5,%6,%7,%8,%9,%10,%11,%12,%13,%14,%15},"
        "{%16,%17,%18,%19}, %20, 0, 1, 1, 1;"
        : "=r"(d[0]), "=r"(d[1]), "=r"(d[2]), "=r"(d[3]), "=r"(d[4]), "=r"(d[5]), "=r"(d[6]), "=r"(d[7]),
          "=r"(d[8]), "=r"(d[9]), "=r"(d[10]), "=r"(d[11]), "=r"(d[12]), "=r"(d[13]), "=r"(d[14]), "=r"(d[15])
        : "r"(a[0]), "r"(a[1]), "r"(a[2]), "r"(a[3]), "l"(desc));
}
template <>
__device__ __forceinline__ void wg_n64_h<1>(uint32_t* d, const uint32_t* a, uint64_t desc) {
    asm volatile("wgmma.mma_async.sync.aligned.m64n64k16.f16.f16.f16 {"
        "%0,%1,%2,%3,%4,%5,%6,%7,%8,%9,%10,%11,%12,%13,%14,%15},"
        "{%16,%17,%18,%19}, %20, 1, 1, 1, 1;"
        : "+r"(d[0]), "+r"(d[1]), "+r"(d[2]), "+r"(d[3]), "+r"(d[4]), "+r"(d[5]), "+r"(d[6]), "+r"(d[7]),
          "+r"(d[8]), "+r"(d[9]), "+r"(d[10]), "+r"(d[11]), "+r"(d[12]), "+r"(d[13]), "+r"(d[14]), "+r"(d[15])
        : "r"(a[0]), "r"(a[1]), "r"(a[2]), "r"(a[3]), "l"(desc));
}
template <int SCALE_D> __device__ __forceinline__ void wg_n96_h(uint32_t* d, const uint32_t* a, uint64_t desc);
template <>
__device__ __forceinline__ void wg_n96_h<0>(uint32_t* d, const uint32_t* a, uint64_t desc) {
    asm volatile("wgmma.mma_async.sync.aligned.m64n96k16.f16.f16.f16 {"
        "%0,%1,%2,%3,%4,%5,%6,%7,%8,%9,%10,%11,%12,%13,%14,%15,"
        "%16,%17,%18,%19,%20,%21,%22,%23},"
        "{%24,%25,%26,%27}, %28, 0, 1, 1, 1;"
        : "=r"(d[0]), "=r"(d[1]), "=r"(d[2]), "=r"(d[3]), "=r"(d[4]), "=r"(d[5]), "=r"(d[6]), "=r"(d[7]),
          "=r"(d[8]), "=r"(d[9]), "=r"(d[10]), "=r"(d[11]), "=r"(d[12]), "=r"(d[13]), "=r"(d[14]), "=r"(d[15]),
          "=r"(d[16]), "=r"(d[17]), "=r"(d[18]), "=r"(d[19]), "=r"(d[20]), "=r"(d[21]), "=r"(d[22]), "=r"(d[23])
        : "r"(a[0]), "r"(a[1]), "r"(a[2]), "r"(a[3]), "l"(desc));
}
template <>
__device__ __forceinline__ void wg_n96_h<1>(uint32_t* d, const uint32_t* a, uint64_t desc) {
    asm volatile("wgmma.mma_async.sync.aligned.m64n96k16.f16.f16.f16 {"
        "%0,%1,%2,%3,%4,%5,%6,%7,%8,%9,%10,%11,%12,%13,%14,%15,"
        "%16,%17,%18,%19,%20,%21,%22,%23},"
        "{%24,%25,%26,%27}, %28, 1, 1, 1, 1;"
        : "+r"(d[0]), "+r"(d[1]), "+r"(d[2]), "+r"(d[3]), "+r"(d[4]), "+r"(d[5]), "+r"(d[6]), "+r"(d[7]),
          "+r"(d[8]), "+r"(d[9]), "+r"(d[10]), "+r"(d[11]), "+r"(d[12]), "+r"(d[13]), "+r"(d[14]), "+r"(d[15]),
          "+r"(d[16]), "+r"(d[17]), "+r"(d[18]), "+r"(d[19]), "+r"(d[20]), "+r"(d[21]), "+r"(d[22]), "+r"(d[23])
        : "r"(a[0]), "r"(a[1]), "r"(a[2]), "r"(a[3]), "l"(desc));
}
template <int SCALE_D> __device__ __forceinline__ void wg_n128_h(uint32_t* d, const uint32_t* a, uint64_t desc);
template <>
__device__ __forceinline__ void wg_n128_h<0>(uint32_t* d, const uint32_t* a, uint64_t desc) {
    asm volatile("wgmma.mma_async.sync.aligned.m64n128k16.f16.f16.f16 {"
        "%0,%1,%2,%3,%4,%5,%6,%7,%8,%9,%10,%11,%12,%13,%14,%15,"
        "%16,%17,%18,%19,%20,%21,%22,%23,%24,%25,%26,%27,%28,%29,%30,%31},"
        "{%32,%33,%34,%35}, %36, 0, 1, 1, 1;"
        : "=r"(d[0]), "=r"(d[1]), "=r"(d[2]), "=r"(d[3]), "=r"(d[4]), "=r"(d[5]), "=r"(d[6]), "=r"(d[7]),
          "=r"(d[8]), "=r"(d[9]), "=r"(d[10]), "=r"(d[11]), "=r"(d[12]), "=r"(d[13]), "=r"(d[14]), "=r"(d[15]),
          "=r"(d[16]), "=r"(d[17]), "=r"(d[18]), "=r"(d[19]), "=r"(d[20]), "=r"(d[21]), "=r"(d[22]), "=r"(d[23]),
          "=r"(d[24]), "=r"(d[25]), "=r"(d[26]), "=r"(d[27]), "=r"(d[28]), "=r"(d[29]), "=r"(d[30]), "=r"(d[31])
        : "r"(a[0]), "r"(a[1]), "r"(a[2]), "r"(a[3]), "l"(desc));
}
template <>
__device__ __forceinline__ void wg_n128_h<1>(uint32_t* d, const uint32_t* a, uint64_t desc) {
    asm volatile("wgmma.mma_async.sync.aligned.m64n128k16.f16.f16.f16 {"
        "%0,%1,%2,%3,%4,%5,%6,%7,%8,%9,%10,%11,%12,%13,%14,%15,"
        "%16,%17,%18,%19,%20,%21,%22,%23,%24,%25,%26,%27,%28,%29,%30,%31},"
        "{%32,%33,%34,%35}, %36, 1, 1, 1, 1;"
        : "+r"(d[0]), "+r"(d[1]), "+r"(d[2]), "+r"(d[3]), "+r"(d[4]), "+r"(d[5]), "+r"(d[6]), "+r"(d[7]),
          "+r"(d[8]), "+r"(d[9]), "+r"(d[10]), "+r"(d[11]), "+r"(d[12]), "+r"(d[13]), "+r"(d[14]), "+r"(d[15]),
          "+r"(d[16]), "+r"(d[17]), "+r"(d[18]), "+r"(d[19]), "+r"(d[20]), "+r"(d[21]), "+r"(d[22]), "+r"(d[23]),
          "+r"(d[24]), "+r"(d[25]), "+r"(d[26]), "+r"(d[27]), "+r"(d[28]), "+r"(d[29]), "+r"(d[30]), "+r"(d[31])
        : "r"(a[0]), "r"(a[1]), "r"(a[2]), "r"(a[3]), "l"(desc));
}
template <int SCALE_D> __device__ __forceinline__ void wg_n192_h(uint32_t* d, const uint32_t* a, uint64_t desc);
template <>
__device__ __forceinline__ void wg_n192_h<0>(uint32_t* d, const uint32_t* a, uint64_t desc) {
    asm volatile("wgmma.mma_async.sync.aligned.m64n192k16.f16.f16.f16 {"
        "%0,%1,%2,%3,%4,%5,%6,%7,%8,%9,%10,%11,%12,%13,%14,%15,"
        "%16,%17,%18,%19,%20,%21,%22,%23,%24,%25,%26,%27,%28,%29,%30,%31,"
        "%32,%33,%34,%35,%36,%37,%38,%39,%40,%41,%42,%43,%44,%45,%46,%47},"
        "{%48,%49,%50,%51}, %52, 0, 1, 1, 1;"
        : "=r"(d[0]), "=r"(d[1]), "=r"(d[2]), "=r"(d[3]), "=r"(d[4]), "=r"(d[5]), "=r"(d[6]), "=r"(d[7]),
          "=r"(d[8]), "=r"(d[9]), "=r"(d[10]), "=r"(d[11]), "=r"(d[12]), "=r"(d[13]), "=r"(d[14]), "=r"(d[15]),
          "=r"(d[16]), "=r"(d[17]), "=r"(d[18]), "=r"(d[19]), "=r"(d[20]), "=r"(d[21]), "=r"(d[22]), "=r"(d[23]),
          "=r"(d[24]), "=r"(d[25]), "=r"(d[26]), "=r"(d[27]), "=r"(d[28]), "=r"(d[29]), "=r"(d[30]), "=r"(d[31]),
          "=r"(d[32]), "=r"(d[33]), "=r"(d[34]), "=r"(d[35]), "=r"(d[36]), "=r"(d[37]), "=r"(d[38]), "=r"(d[39]),
          "=r"(d[40]), "=r"(d[41]), "=r"(d[42]), "=r"(d[43]), "=r"(d[44]), "=r"(d[45]), "=r"(d[46]), "=r"(d[47])
        : "r"(a[0]), "r"(a[1]), "r"(a[2]), "r"(a[3]), "l"(desc));
}
template <>
__device__ __forceinline__ void wg_n192_h<1>(uint32_t* d, const uint32_t* a, uint64_t desc) {
    asm volatile("wgmma.mma_async.sync.aligned.m64n192k16.f16.f16.f16 {"
        "%0,%1,%2,%3,%4,%5,%6,%7,%8,%9,%10,%11,%12,%13,%14,%15,"
        "%16,%17,%18,%19,%20,%21,%22,%23,%24,%25,%26,%27,%28,%29,%30,%31,"
        "%32,%33,%34,%35,%36,%37,%38,%39,%40,%41,%42,%43,%44,%45,%46,%47},"
        "{%48,%49,%50,%51}, %52, 1, 1, 1, 1;"
        : "+r"(d[0]), "+r"(d[1]), "+r"(d[2]), "+r"(d[3]), "+r"(d[4]), "+r"(d[5]), "+r"(d[6]), "+r"(d[7]),
          "+r"(d[8]), "+r"(d[9]), "+r"(d[10]), "+r"(d[11]), "+r"(d[12]), "+r"(d[13]), "+r"(d[14]), "+r"(d[15]),
          "+r"(d[16]), "+r"(d[17]), "+r"(d[18]), "+r"(d[19]), "+r"(d[20]), "+r"(d[21]), "+r"(d[22]), "+r"(d[23]),
          "+r"(d[24]), "+r"(d[25]), "+r"(d[26]), "+r"(d[27]), "+r"(d[28]), "+r"(d[29]), "+r"(d[30]), "+r"(d[31]),
          "+r"(d[32]), "+r"(d[33]), "+r"(d[34]), "+r"(d[35]), "+r"(d[36]), "+r"(d[37]), "+r"(d[38]), "+r"(d[39]),
          "+r"(d[40]), "+r"(d[41]), "+r"(d[42]), "+r"(d[43]), "+r"(d[44]), "+r"(d[45]), "+r"(d[46]), "+r"(d[47])
        : "r"(a[0]), "r"(a[1]), "r"(a[2]), "r"(a[3]), "l"(desc));
}

#define HINT 0
constexpr uint64_t POL_EF = 0x12F0000000000000ull;
__device__ __forceinline__ void wg_fence() { asm volatile("wgmma.fence.sync.aligned;" ::: "memory"); }
__device__ __forceinline__ void wg_commit() { asm volatile("wgmma.commit_group.sync.aligned;" ::: "memory"); }
template <int N> __device__ __forceinline__ void wg_wait() { asm volatile("wgmma.wait_group.sync.aligned %0;" ::"n"(N) : "memory"); }
template <int N> __device__ __forceinline__ void pin(uint32_t* r) {
#pragma unroll
    for (int i = 0; i < N; i++) asm volatile("" : "+r"(r[i])::"memory");
}
__device__ __forceinline__ void sbar() { asm volatile("griddepcontrol.launch_dependents;" ::: "memory"); }

#define CK64 0
__device__ __forceinline__ void cfence(uint32_t& sink) {
    uint32_t ck;
    asm volatile("mov.u32 %0, %%clock;" : "=r"(ck)::"memory");
    sink ^= ck;
}
#define SFT 0
__device__ __forceinline__ void bar_sync(int id, int n) { asm volatile("bar.sync %0, %1;" ::"r"(id), "r"(n) : "memory"); }
__device__ __forceinline__ void bar_arrive(int id, int n) { asm volatile("bar.arrive %0, %1;" ::"r"(id), "r"(n) : "memory"); }
#define BARP 3
template <int ID> __device__ __forceinline__ void bar_sync_wg(int wg) {
    if (BARP & 1) asm volatile("{.reg .pred p; setp.ne.u32 p, %0, 0; @p bar.sync %2, 256; @!p bar.sync %1, 256;}" ::"r"(wg), "n"(ID), "n"(ID + 1) : "memory");
    else bar_sync(ID + wg, 256);
}
template <int ID> __device__ __forceinline__ void bar_arrive_wg(int wg) {
    if (BARP & 2) asm volatile("{.reg .pred p; setp.ne.u32 p, %0, 0; @p bar.arrive %2, 256; @!p bar.arrive %1, 256;}" ::"r"(wg), "n"(ID), "n"(ID + 1) : "memory");
    else bar_arrive(ID + wg, 256);
}
__device__ __forceinline__ void mbar_init(uint32_t a, uint32_t cnt) { asm volatile("mbarrier.init.shared::cta.b64 [%0], %1;" ::"r"(a), "r"(cnt) : "memory"); }
__device__ __forceinline__ void mbar_expect_tx(uint32_t a, uint32_t bytes) { asm volatile("mbarrier.arrive.expect_tx.shared::cta.b64 _, [%0], %1;" ::"r"(a), "r"(bytes) : "memory"); }
__device__ __forceinline__ bool mbar_try(uint32_t a, uint32_t parity) {
    uint32_t ok;
    asm volatile("{.reg .pred p; mbarrier.try_wait.parity.shared::cta.b64 p, [%1], %2; selp.u32 %0, 1, 0, p;}" : "=r"(ok) : "r"(a), "r"(parity) : "memory");
    return ok;
}
__device__ __forceinline__ void mbar_wait(uint32_t a, uint32_t parity) {
    asm volatile("{.reg .pred p, q; .reg .u32 g; mov.u32 g, 0;\n"
                 "L: mbarrier.try_wait.parity.shared::cta.b64 p, [%0], %1;\n"
                 "add.u32 g, g, 1; setp.lt.and.u32 q, g, 0x400000, !p; @q bra L;}" ::"r"(a), "r"(parity) : "memory");
}
__device__ __forceinline__ bool mbar_test(uint32_t a, uint32_t parity) {
    uint32_t ok;
    asm volatile("{.reg .pred p; mbarrier.test_wait.parity.shared::cta.b64 p, [%1], %2; selp.u32 %0, 1, 0, p;}" : "=r"(ok) : "r"(a), "r"(parity) : "memory");
    return ok;
}
__device__ __forceinline__ bool elect() {
    uint32_t ok;
    asm volatile("{.reg .pred p; elect.sync _|p, 0xffffffff; selp.u32 %0, 1, 0, p;}" : "=r"(ok));
    return ok;
}
__device__ __forceinline__ void tma_x(const CUtensorMap* tm, int slot, int q, int xq, int yq) {
    const uint32_t bar = S_BAR + 8 * slot;
    mbar_expect_tx(bar, XSTG / 4);
    asm volatile("cp.async.bulk.tensor.3d.shared::cluster.global.mbarrier::complete_tx::bytes [%0], [%1, {%3, %4, %5}], [%2];"
                 ::"r"(S_X + slot * XSTG + q * (XSTG / 4)), "l"(tm), "r"(bar), "r"(0), "r"(xq), "r"(yq) : "memory");
}
__device__ __forceinline__ void bulk_load(uint32_t dst, const void* src, uint32_t bytes, uint32_t bar) {
    asm volatile("cp.async.bulk.shared::cluster.global.mbarrier::complete_tx::bytes [%0], [%1], %2, [%3];"
                 ::"r"(dst), "l"(src), "r"(bytes), "r"(bar) : "memory");
}
__device__ __forceinline__ uint32_t lds32(uint32_t a) { uint32_t v; asm volatile("ld.shared.b32 %0, [%1];" : "=r"(v) : "r"(a)); return v; }
__device__ __forceinline__ void lds128(uint32_t* r, uint32_t a) { asm volatile("ld.shared.v4.b32 {%0,%1,%2,%3}, [%4];" : "=r"(r[0]), "=r"(r[1]), "=r"(r[2]), "=r"(r[3]) : "r"(a)); }
__device__ __forceinline__ void sts32(uint32_t a, uint32_t v) { asm volatile("st.shared.b32 [%0], %1;" ::"r"(a), "r"(v)); }
__device__ __forceinline__ void sts128(uint32_t a, uint32_t x, uint32_t y, uint32_t z, uint32_t w) { asm volatile("st.shared.v4.b32 [%0], {%1,%2,%3,%4};" ::"r"(a), "r"(x), "r"(y), "r"(z), "r"(w)); }
__device__ __forceinline__ void ldsm4(uint32_t* r, uint32_t a) {
    asm volatile("ldmatrix.sync.aligned.m8n8.x4.shared.b16 {%0,%1,%2,%3}, [%4];" : "=r"(r[0]), "=r"(r[1]), "=r"(r[2]), "=r"(r[3]) : "r"(a));
}
__device__ __forceinline__ void ldsm4s(uint32_t& r0, uint32_t& r1, uint32_t& r2, uint32_t& r3, uint32_t a) {
    asm volatile("ldmatrix.sync.aligned.m8n8.x4.shared.b16 {%0,%1,%2,%3}, [%4];" : "=r"(r0), "=r"(r1), "=r"(r2), "=r"(r3) : "r"(a));
}
__device__ __forceinline__ void ldsm2s(uint32_t& r0, uint32_t& r1, uint32_t a) {
    asm volatile("ldmatrix.sync.aligned.m8n8.x2.shared.b16 {%0,%1}, [%2];" : "=r"(r0), "=r"(r1) : "r"(a));
}
__device__ __forceinline__ void stsm4(uint32_t a, const uint32_t* r) {
    asm volatile("stmatrix.sync.aligned.m8n8.x4.shared.b16 [%4], {%0,%1,%2,%3};" ::"r"(r[0]), "r"(r[1]), "r"(r[2]), "r"(r[3]), "r"(a));
}
__device__ __forceinline__ void ldg128(uint32_t* r, const void* p) {
    asm volatile("ld.global.nc.L1::no_allocate.v4.b32 {%0,%1,%2,%3}, [%4];" : "=r"(r[0]), "=r"(r[1]), "=r"(r[2]), "=r"(r[3]) : "l"(p));
}
__device__ __forceinline__ void stg128(void* p, uint32_t x, uint32_t y, uint32_t z, uint32_t w) {
    asm volatile("st.global.L1::no_allocate.v4.b32 [%0], {%1,%2,%3,%4};" ::"l"(p), "r"(x), "r"(y), "r"(z), "r"(w));
}
__device__ __forceinline__ uint32_t bfma(uint32_t a, uint32_t b, uint32_t c) { uint32_t d; asm("fma.rn.bf16x2 %0, %1, %2, %3;" : "=r"(d) : "r"(a), "r"(b), "r"(c)); return d; }
__device__ __forceinline__ uint32_t bmul(uint32_t a, uint32_t b) { uint32_t d; asm("mul.rn.bf16x2 %0, %1, %2;" : "=r"(d) : "r"(a), "r"(b)); return d; }
__device__ __forceinline__ uint32_t vfma(uint32_t a, uint32_t b, uint32_t c) { uint32_t d; asm volatile("fma.rn.bf16x2 %0, %1, %2, %3;" : "=r"(d) : "r"(a), "r"(b), "r"(c)); return d; }
__device__ __forceinline__ void vacc(uint32_t& d, uint32_t a, uint32_t b) { asm volatile("fma.rn.bf16x2 %0, %1, %2, %0;" : "+r"(d) : "r"(a), "r"(b)); }
__device__ __forceinline__ uint32_t vadd(uint32_t a, uint32_t b) { uint32_t d; asm volatile("add.rn.bf16x2 %0, %1, %2;" : "=r"(d) : "r"(a), "r"(b)); return d; }
__device__ __forceinline__ uint32_t vsub(uint32_t a, uint32_t b) { uint32_t d; asm volatile("sub.rn.bf16x2 %0, %1, %2;" : "=r"(d) : "r"(a), "r"(b)); return d; }
__device__ __forceinline__ uint32_t vmul(uint32_t a, uint32_t b) { uint32_t d; asm volatile("mul.rn.bf16x2 %0, %1, %2;" : "=r"(d) : "r"(a), "r"(b)); return d; }
__device__ __forceinline__ uint32_t badd(uint32_t a, uint32_t b) { uint32_t d; asm("add.rn.bf16x2 %0, %1, %2;" : "=r"(d) : "r"(a), "r"(b)); return d; }
__device__ __forceinline__ uint32_t habsmax(uint32_t a, uint32_t b) { uint32_t d; asm("max.xorsign.abs.bf16x2 %0, %1, %2;" : "=r"(d) : "r"(a), "r"(b)); return d; }
__device__ __forceinline__ float bf_lo2(uint32_t v) { return __uint_as_float(v << 16); }
__device__ __forceinline__ float bf_lo(uint32_t v) { uint32_t d; asm("prmt.b32 %0, %1, 0, 0x1044;" : "=r"(d) : "r"(v)); return __uint_as_float(d); }
__device__ __forceinline__ float bf_hi(uint32_t v) { return __uint_as_float(v & 0xffff0000u); }
__device__ __forceinline__ uint32_t pack_h2(float lo, float hi) { uint32_t d; asm("cvt.rn.f16x2.f32 %0, %1, %2;" : "=r"(d) : "f"(hi), "f"(lo)); return d; }
__device__ __forceinline__ uint32_t pack_h2z(float lo, float hi) { uint32_t d; asm("cvt.rz.f16x2.f32 %0, %1, %2;" : "=r"(d) : "f"(hi), "f"(lo)); return d; }
__device__ __forceinline__ uint32_t b2h(uint32_t v) { return v + 7u * (v & 0x7fff7fffu); }
__device__ __forceinline__ uint32_t pack_b2(float lo, float hi) { uint32_t d; asm("cvt.rn.bf16x2.f32 %0, %1, %2;" : "=r"(d) : "f"(hi), "f"(lo)); return d; }

template <int N> __device__ __forceinline__ void gelu(uint32_t* h) {
#pragma unroll
    for (int i = 0; i < N; i++) {
        uint32_t p, u, t;
        asm("fma.rn.f16x2 %0, %1, %1, %2;" : "=r"(p) : "r"(h[i]), "r"(GK2));
        asm("mul.rn.f16x2 %0, %1, %2;" : "=r"(u) : "r"(h[i]), "r"(p));
        asm("tanh.approx.f16x2 %0, %1;" : "=r"(t) : "r"(u));
        asm("fma.rn.f16x2 %0, %1, %2, %1;" : "=r"(h[i]) : "r"(h[i]), "r"(t));
    }
    pin<N>(h);
}
#define NUP 3
template <int N> __device__ __forceinline__ void gelu_a(uint32_t* t, const uint32_t* h) {
#pragma unroll
    for (int i = 0; i < N; i++) {
        uint32_t p, u;
        asm("fma.rn.f16x2 %0, %1, %1, %2;" : "=r"(p) : "r"(h[i]), "r"(GK2));
        asm("mul.rn.f16x2 %0, %1, %2;" : "=r"(u) : "r"(h[i]), "r"(p));
        if (i < N - NUP) {
            uint32_t a, b;
            asm("{.reg .b16 l, h, x; mov.b32 {l, h}, %2; tanh.approx.f16 x, l; cvt.u32.u16 %0, x; tanh.approx.f16 x, h; cvt.u32.u16 %1, x;}" : "=r"(a), "=r"(b) : "r"(u));
            asm volatile("prmt.b32 %0, %1, %2, 0x5410;" : "=r"(t[i]) : "r"(a), "r"(b));
        } else asm("tanh.approx.f16x2 %0, %1;" : "=r"(t[i]) : "r"(u));
    }
    pin<N>(t);
}
template <int N> __device__ __forceinline__ void gelu_b(uint32_t* h, const uint32_t* t) {
#pragma unroll
    for (int i = 0; i < N; i++) asm volatile("fma.rn.f16x2 %0, %1, %2, %1;" : "=r"(h[i]) : "r"(h[i]), "r"(t[i]));
}
#define RESCARRY 1
#define MIDW 12
#define OV 1
#define SB2 SB1
#define SB3 SB1
#define SB1 cfence(sink);

#define PEEL0 1
#define PEEL1 1
#define EDGE1 1
#define PRO 2
#define XFIRST 2
#define XSECOND 3
#define W2BITS 3
constexpr uint32_t W2MSK = ((1u << W2BITS) - 1) * 0x10001u, W2RND = (1u << W2BITS >> 1) * 0x10001u;
#define NOCNT 1
#define PAD 0
#define SWAPB 0
#define WCVT 3
#define PAIR 1
#define EARLY 1
#define TAPF 1
#define ADDR 1
#define VT 1
#define PEELT 1
#define CSINK lane
#define CFT 1
#define CORDER 1
template <int S, int P, int ILO, int IHI>
__device__ __forceinline__ void conv_col(uint32_t x, const uint32_t* w, uint32_t (&acc)[4][S], uint32_t (&o)[S]) {
#pragma unroll
    for (int j = 4; j >= 0; j--) {
        const int q = P - j;
        if (q < 0 || q >= S) continue;
#pragma unroll
        for (int i = IHI; i >= ILO; i--) {
            uint32_t& d = (i == 4) ? o[q] : acc[i == 4 ? 0 : 3 - i][q];
            const uint32_t ww = w[2 * (i * 5 + j)];
            if (j > 0) vacc(d, x, ww);
            else if (i == 4 && CORDER == 1) { d = acc[0][q]; vacc(d, x, ww); }
            else d = (i == 0) ? vmul(x, ww) : vfma(x, ww, acc[i == 0 ? 0 : 4 - i][q]);
        }
    }
}
#define CFENCE 0x13a
#define FFB 1
struct Conv {
    uint32_t w[50];
    uint32_t s[20];
    uint32_t accA[4][8], accB[4][4];
    uint32_t sink;
    uint32_t xa[2][12], xb[2][8];
};
template <int S, int P, int MODE, int WS>
__device__ __forceinline__ void tap_col(uint32_t x, const uint32_t* w, uint32_t (&d)[S], const uint32_t (&src)[S]) {
#pragma unroll
    for (int j = 4; j >= 0; j--) {
        const int q = P - j;
        if (q < 0 || q >= S) continue;
        if (j > 0 || MODE == 0) vacc(d[q], x, w[WS * j]);
        else if (MODE == 1) d[q] = vmul(x, w[0]);
        else d[q] = vfma(x, w[0], src[q]);
    }
}
template <int R, int K> __device__ __forceinline__ void conv_ld(Conv& c, uint32_t a1) {
    ldsm4s(c.xa[R][2 * K + 2], c.xb[R][2 * K], c.xa[R][2 * K + 3], c.xb[R][2 * K + 1], a1 + K * 2 * CH * 2);
}
#define CFN(n) { if ((CFENCE >> n) & 1) cfence(c.sink); }
#define ALLCOLS CA(0); CA(1); CA(2); CB(0); CA(3); CB(1); CA(4); CB(2); CA(5); CB(3); CA(6); CB(4); CA(7); CB(5); CA(8); CB(6); CA(9); CB(7); CA(10); CA(11);
template <int R, typename Fn>
__device__ __forceinline__ void conv_out(Conv& c, uint32_t sA, uint32_t sB, Fn before_store) {
    constexpr int RB_ = FFB ? R : 0;
#define CA(p) tap_col<8, p, 0, 2>(c.xa[R][p], c.w + 41, c.accA[R], c.accA[R])
#define CB(p) tap_col<4, p, 0, 2>(c.xb[R][p], c.w + 40, c.accB[RB_], c.accB[RB_])
    CA(0); CA(1); CA(2); CB(0); CA(3); CB(1); CA(4); CB(2); CA(5); CB(3); CA(6); CB(4); CA(7); CB(5);
    before_store();
    stsm4(sA, c.accA[R]);
    CA(8); CB(6); CA(9); CB(7); CA(10); CA(11);
    stsm4(sB, c.accB[RB_]);
    stsm4(sA + 4 * CPITCH, c.accA[R] + 4);
#undef CA
#undef CB
}
template <int S, int P, int R, bool OLD, bool NEW>
__device__ __forceinline__ void dcol(const uint32_t (&x)[2][S + 4], const uint32_t* w, uint32_t (&acc)[4][S]) {
    if (!OLD && !NEW) return;
    const uint32_t d = vsub(x[0][P], x[1][P]);
    if (R == 1) {
        if (OLD) tap_col<S, P, 0, 2>(d, w + 20, acc[0], acc[0]);
        if (NEW) tap_col<S, P, 2, 2>(d, w, acc[2], acc[3]);
    } else {
        if (OLD) tap_col<S, P, 0, 2>(d, w + 30, acc[1], acc[1]);
        if (NEW) tap_col<S, P, 0, 2>(d, w + 10, acc[3], acc[3]);
    }
}
template <int R, int ILO, int IHI, bool OLD, bool NEW, typename Fn>
__device__ __forceinline__ void conv_rest(Conv& c, uint32_t a1, uint32_t a2, Fn mid) {
    if (R == 1) {
        if (OLD) {
#define CA(p) tap_col<8, p, 1, 2>(c.xa[1][p], c.s + 11, c.accA[0], c.accA[0])
#define CB(p) { if (FFB) tap_col<4, p, 1, 2>(c.xb[1][p], c.s + 10, c.accB[0], c.accB[0]); }
            ALLCOLS
#undef CA
#undef CB
#pragma unroll
            for (int q = 0; q < 8; q++) { c.accA[1][q] = vadd(c.accA[3][q], c.accA[0][q]); c.accA[0][q] = vadd(c.accA[2][q], c.accA[0][q]); }
#pragma unroll
            for (int q = 0; q < 4 * FFB; q++) { c.accB[1][q] = vadd(c.accB[3][q], c.accB[0][q]); c.accB[0][q] = vadd(c.accB[2][q], c.accB[0][q]); }
            CFN(7)
        }
        if (NEW) {
#define CA(p) tap_col<8, p, 1, 2>(c.xa[1][p], c.s + 1, c.accA[3], c.accA[3])
#define CB(p) { if (FFB) tap_col<4, p, 1, 2>(c.xb[1][p], c.s, c.accB[3], c.accB[3]); }
            ALLCOLS
#undef CA
#undef CB
            CFN(8)
        }
    }
#define CA(p) dcol<8, p, R, OLD, NEW>(c.xa, c.w + 1, c.accA)
#define CB(p) { if (FFB) dcol<4, p, R, OLD, NEW>(c.xb, c.w, c.accB); }
    CA(0); CA(1); CFN(0)
    ldsm2s(c.xa[1 - R][0], c.xa[1 - R][1], a2);
    CA(2); CB(0); CA(3); CB(1); CFN(1)
    conv_ld<1 - R, 0>(c, a1);
    CA(4); CB(2); CA(5); CB(3); CFN(2)
    conv_ld<1 - R, 1>(c, a1);
    CA(6); CB(4); CA(7); CB(5); CFN(3)
    conv_ld<1 - R, 2>(c, a1);
    CA(8); CB(6); CA(9); CB(7); CFN(4)
    conv_ld<1 - R, 3>(c, a1);
    CA(10); CA(11); CFN(5)
    ldsm2s(c.xa[1 - R][10], c.xa[1 - R][11], a2 + 10 * CH * 2);
    mid();
    CFN(9)
#undef CA
#undef CB
    if (!FFB) {
        uint32_t oB[4];
#define CB(p) conv_col<4, p, ILO, IHI>(c.xb[R][p], c.w, c.accB, oB)
        CB(0); CB(1); CB(2); CB(3); CB(4); CB(5); CB(6); CB(7);
#undef CB
        CFN(10)
    }
}

__device__ __forceinline__ uint64_t mkd(uint64_t db, uint32_t lo) { uint64_t d; asm volatile("add.u64 %0, %1, %2;" : "=l"(d) : "l"(db), "l"((uint64_t)lo)); return d; }
template <int J, int K0, int K1> __device__ __forceinline__ void gemm1(uint32_t* H, const uint32_t* a1, uint64_t db) {
#pragma unroll
    for (int kk = K0; kk < K1; kk++) {
        const uint64_t d = mkd(db, D1 + ((2 * kk * 48 + J * (CN / 8)) * 128 >> 4));
        if (kk == 0) wg_n96_h<0>(H + J * 24, a1, d);
        else wg_n96_h<1>(H + J * 24, a1 + 4 * kk, d);
    }
}
template <int K0, int K1> __device__ __forceinline__ void gemm2(uint32_t* acc, const uint32_t* H, uint64_t db) {
#pragma unroll
    for (int ks = K0; ks < K1; ks++) {
        const uint64_t d = mkd(db, D2 + (2 * ks * 12 * 128 >> 4));
        if (ks == 0) wg_n96_h<0>(acc, H, d);
        else wg_n96_h<1>(acc, H + 4 * ks, d);
    }
}

__device__ __forceinline__ float quad_sum(uint32_t v) {
    float s = bf_lo(v) + bf_hi(v);
    s += __shfl_xor_sync(0xffffffffu, s, 1);
    s += __shfl_xor_sync(0xffffffffu, s, 2);
    return s;
}
template <int r> __device__ __forceinline__ void ln_part(const uint32_t* a, uint32_t* sq) {
    uint32_t s[6], q[2];
#pragma unroll
    for (int i = 0; i < 6; i++) s[i] = badd(a[4 * i + r], a[4 * i + 2 + r]);
    sq[r] = badd(badd(badd(s[0], s[1]), badd(s[2], s[3])), badd(s[4], s[5]));
#pragma unroll
    for (int i = 0; i < 12; i++) q[i & 1] = (i < 2) ? bmul(a[2 * i + r], a[2 * i + r]) : bfma(a[2 * i + r], a[2 * i + r], q[i & 1]);
    sq[2 + r] = badd(q[0], q[1]);
    pin<1>(sq + r); pin<1>(sq + 2 + r);
}
__device__ __forceinline__ void ln_mma(float* d, const uint32_t* sq, uint64_t db) {
    asm volatile("wgmma.mma_async.sync.aligned.m64n8k16.f32.bf16.bf16 {%0,%1,%2,%3}, {%4,%5,%6,%7}, %8, 0, 1, 1, 1;"
                 : "=f"(d[0]), "=f"(d[1]), "=f"(d[2]), "=f"(d[3]) : "r"(sq[0]), "r"(sq[1]), "r"(sq[2]), "r"(sq[3]), "l"(mkd(db, D3)));
}
__device__ __forceinline__ float rsq(float v) { float r; asm("rsqrt.approx.ftz.f32 %0, %1;" : "=f"(r) : "f"(v)); return r; }
__device__ __forceinline__ bool ln_fin(float* d, uint32_t* st) {
    asm volatile("" : "+f"(d[0]), "+f"(d[1]), "+f"(d[2]), "+f"(d[3])::"memory");
    bool risky = false;
#pragma unroll
    for (int r = 0; r < 2; r++) {
        const float q = rsq(fmaf(-d[2 * r], d[2 * r], d[2 * r + 1] + LN_EPS * (CH * CH)));
        const float z = d[2 * r] * q;
        risky |= !(fabsf(z) <= 1.f);
        st[r] = pack_b2(q * (LN_OUT * CH), z * -LN_OUT);
    }
    pin<2>(st);
    return __any_sync(0xffffffffu, risky);
}
__device__ __forceinline__ void ln_fix(uint32_t* a, const float* d, uint32_t* st) {
#pragma unroll
    for (int r = 0; r < 2; r++) {
        const uint32_t m2 = pack_b2(d[2 * r] * (-1.f / CH), d[2 * r] * (-1.f / CH));
        uint32_t q[2];
#pragma unroll
        for (int i = 0; i < 12; i++) {
            a[2 * i + r] = badd(a[2 * i + r], m2);
            q[i & 1] = (i < 2) ? bmul(a[2 * i + r], a[2 * i + r]) : bfma(a[2 * i + r], a[2 * i + r], q[i & 1]);
        }
        st[r] = pack_b2(rsq(fmaf(quad_sum(badd(q[0], q[1])), 1.f / CH, LN_EPS)) * LN_OUT, 0.f);
    }
}
template <int I0, int I1> __device__ __forceinline__ void ln_out(uint32_t* a, const uint32_t* b, const uint32_t* st) {
#pragma unroll
    for (int i = I0; i < I1; i++) {
        uint32_t v;
        asm("{.reg .b16 l, h; .reg .b32 ll, hh; mov.b32 {l, h}, %2; mov.b32 ll, {l, l}; mov.b32 hh, {h, h}; fma.rn.bf16x2 %0, %1, ll, hh;}"
            : "=r"(v) : "r"(b[i]), "r"(st[i & 1]));
        a[i] = v + 7u * (v & 0x7fff7fffu);
        pin<1>(a + i);
    }
}

__device__ __forceinline__ void epi_cvt(uint32_t* e, const uint32_t* acc) {
#pragma unroll
    for (int i = 0; i < 24; i++) {
        const uint32_t hv = acc[i];
        const float2 f = __half22float2(*reinterpret_cast<const __half2*>(&hv));
        e[i] = pack_b2(f.x, f.y);
    }
    pin<24>(e);
}
template <int R> __device__ __forceinline__ void epi_out(const uint32_t* e, const uint32_t* res, uint32_t osc2, uint8_t* gp, bool on) {
#pragma unroll
    for (int i = 0; i < 3; i++) {
        uint32_t o[4];
#pragma unroll
        for (int jj = 0; jj < 4; jj++) o[jj] = vfma(e[2 * (4 * i + jj) + R], osc2, res[(R * 3 + i) * 4 + jj]);
        asm volatile("{.reg .pred p; setp.ne.u32 p, %5, 0; @p st.global.L1::no_allocate.v4.b32 [%0], {%1,%2,%3,%4};}"
                     ::"l"(gp + R * 8 * CH * 2 + i * 64), "r"(o[0]), "r"(o[1]), "r"(o[2]), "r"(o[3]), "r"((uint32_t)(on && (!(HINT & 8) || osc2 == 0))));
    }
}
template <int R> __device__ __forceinline__ void load_res(uint32_t* res, const uint8_t* xg) {
#pragma unroll
    for (int i = 0; i < 3; i++) ldg128(res + (R * 3 + i) * 4, xg + R * 8 * CH * 2 + i * 64);
}

#define CYS(k)
#define TLREC(role, idx)
#define TLRECG(role, idx)

constexpr int TSTEP = 2 * NWG * IMG_W * CH * 2;

__global__ void __launch_bounds__(384, 1)
replk_kernel(const __grid_constant__ CUtensorMap tmx, const uint8_t* __restrict__ x, const uint8_t* __restrict__ dwl,
             const uint8_t* __restrict__ dws, const uint8_t* __restrict__ w1, const uint8_t* __restrict__ w2,
             uint8_t* __restrict__ out, const uint64_t db) {
    extern __shared__ __align__(1024) uint8_t smem[];
#define ROT 2
    const int tid = (threadIdx.x + ROT * 128) % 384, lane = tid & 31;
    const int warp = __shfl_sync(0xffffffffu, tid >> 5, 0);
    const int w0 = (blockIdx.x % (IMG_W / SW)) * SW, y0 = (blockIdx.x / (IMG_W / SW)) * RB;
    const int up = PAIR & ~(blockIdx.x / (IMG_W / SW));
    const int dy = 1 - 2 * up, yb = y0 - 2 + (RB + 3) * up;
    if (warp < 8) { TLREC(warp >> 2, 0); TLRECG(warp >> 2, 78); }
    auto first_loads = [&] {
        if ((uint32_t)__cvta_generic_to_shared(smem) != SB) __trap();
#pragma unroll
        for (int s = 0; s < NS; s++) mbar_init(S_BAR + 8 * s, 4);
        asm volatile("fence.mbarrier_init.release.cluster;" ::: "memory");
        TLREC(3, 43);
        if (EARLY) {
#pragma unroll
            for (int q = 0; q < 4; q++) tma_x(&tmx, 0, q, w0 - 2 + (q & 1) * 18, yb + dy * (q >> 1));
        }
        TLREC(3, 44);
    };

    if (warp >= 8) {
        const int cw = warp - 8;
        const int tj = min((tid - 256) / 24, 4), tc = (tid - 256) % 24;
        uint2 ts[5], tl[3];
        auto tap_loads = [&] {
#pragma unroll
            for (int i = 0; i < 5; i++) ts[i] = __ldg(reinterpret_cast<const uint2*>(dws) + ((2 + dy * (i - 2)) * 5 + tj) * 24 + tc);
#pragma unroll
            for (int i = 0; i < 3; i++) tl[i] = __ldg(reinterpret_cast<const uint2*>(dwl) + ((1 + dy * (i - 1)) * 3 + (tj + 2) % 3) * 24 + tc);
        };
        if (TAPF) tap_loads();
        if (cw == 0 && elect()) first_loads();
        bar_sync(BAR_CV, 128);
        const int xq = w0 - 2 + (cw & 1) * 18, yq = yb + dy * (cw >> 1);
        if (elect()) {
#pragma unroll
            for (int s = EARLY; s < XFIRST; s++) tma_x(&tmx, s, cw, xq, yq + 2 * dy * s);
        }
        TLREC(3, 45);
        if (!TAPF) tap_loads();
        if (PRO & 1) bar_arrive(0, 160);
        Conv c;
        {
            TLREC(3, 47);
            const uint32_t lm = (tj & 3) ? ~0u : 0u;
            uint32_t v[7][2];
#pragma unroll
            for (int i = 0; i < 5; i++) {
                v[i][0] = ts[i].x; v[i][1] = ts[i].y;
                if (i >= 1 && i <= 3) { v[i][0] = badd(v[i][0], tl[i - 1].x & lm); v[i][1] = badd(v[i][1], tl[i - 1].y & lm); }
                v[i][0] = bmul(v[i][0], WSC2); v[i][1] = bmul(v[i][1], WSC2);
            }
#pragma unroll
            for (int u = 0; u < 2; u++) { v[5][u] = badd(v[0][u], v[1][u]); v[6][u] = badd(v[2][u], v[3][u]); }
#pragma unroll
            for (int i = 0; i < 7; i++)
                asm volatile("st.shared.v2.b32 [%0], {%1, %2};" ::"r"(S_C + ((i * 5 + tj) * 24 + tc) * 8), "r"(v[i][0]), "r"(v[i][1]) : "memory");
            bar_sync(BAR_CV, 128);
            TLREC(3, 40);
            if (elect()) {
#pragma unroll
                for (int s = XFIRST; s < XSECOND; s++) tma_x(&tmx, s, cw, xq, yq + 2 * dy * s);
            }
            const int qd = lane & 7, u = (lane >> 3) & 1;
            const uint32_t ws = S_C + ((cw < 2 + u) ? qd : 8 + (qd & 3)) * 16;
#pragma unroll
            for (int k = 0; k < 12; k++) ldsm4(c.w + 4 * k, ws + ((lane >> 4) + 2 * k) * CH * 2);
            ldsm2s(c.w[48], c.w[49], ws + 24 * CH * 2);
#pragma unroll
            for (int k = 0; k < 5; k++) ldsm4(c.s + 4 * k, ws + ((lane >> 4) + 25 + 2 * k) * CH * 2);
        }
        const int mi = lane >> 3, qd = lane & 7;
        const int chA = (cw < 3) ? qd : 8 + (qd & 3), pxA = (cw < 3) ? 8 * cw : 16 * (qd >> 2);
        const int chB = (cw < 2) ? qd : 8 + (qd & 3), pxB = (cw < 2) ? 24 + 4 * cw : 16 * (qd >> 2) + 8 + 4 * (cw - 2);
        const uint32_t a1 = S_X + ((mi & 1) ? (pxB + (mi >> 1)) * (CH * 2) + chB * 16 : (pxA + 2 + (mi >> 1)) * (CH * 2) + chA * 16);
        const uint32_t a2 = S_X + (pxA + (mi & 1)) * (CH * 2) + chA * 16;
        const uint32_t sA = S_C + (pxA >> 4) * CGRP + ((pxA & 15) + mi) * CPITCH + chA * 16;
        const uint32_t sB = S_C + (pxB >> 4) * CGRP + ((pxB & 15) + mi) * CPITCH + chB * 16;
        auto nop = [] {};
        c.sink = CSINK;
        TLREC(3, 1); CYS(0)
        mbar_wait(S_BAR, 0);
        ldsm2s(c.xa[0][0], c.xa[0][1], a2);
        conv_ld<0, 0>(c, a1); conv_ld<0, 1>(c, a1); conv_ld<0, 2>(c, a1); conv_ld<0, 3>(c, a1);
        ldsm2s(c.xa[0][10], c.xa[0][11], a2 + 10 * CH * 2);
        TLREC(3, 41);
        conv_rest<0, 0, 0, false, false>(c, a1 + XROW, a2 + XROW, nop);
        if (elect()) {
#pragma unroll
            for (int s = XSECOND; s < 4; s++) tma_x(&tmx, s, cw, xq, yq + 2 * dy * s);
        }
        mbar_wait(S_BAR + 8, 0);
        TLREC(3, 42); CYS(1)
        conv_rest<1, 0, 1, false, true>(c, a1 + XSTG, a2 + XSTG, nop);
        conv_rest<0, 0, 2, false, true>(c, a1 + XSTG + XROW, a2 + XSTG + XROW, nop);
        TLREC(3, 2);
        bar_sync(BAR_CV, 128);
        if (elect()) tma_x(&tmx, 0, cw, xq, yq + 8 * dy);
        mbar_wait(S_BAR + 16, 0);
        TLREC(3, 3); CYS(2)
        uint32_t u, dy2, xd0;
        uint64_t tm;
        asm volatile("mov.u32 %0, 24;" : "=r"(u));
        asm volatile("mov.u32 %0, %1;" : "=r"(dy2) : "r"(2 * dy));
        asm volatile("mov.u32 %0, %1;" : "=r"(xd0) : "r"(S_X + cw * (XSTG / 4) - S_BAR * (XSTG / 8)));
        asm volatile("mov.u64 %0, %1;" : "=l"(tm) : "l"(&tmx));
        uint32_t xo = 2 * XSTG, qA = sA, qB = sB;
        int dq = CBUF;
#define p1 (a1 + xo)
#define p2 (a2 + xo)
        int yn = yq + 10 * dy;
        uint32_t bid = BAR_EMPTY + (lane >> 5);
#pragma unroll 1
        for (;;) {
            const uint32_t nb = S_BAR | (u & 24), np = u >> 5;
            bool ok;
            conv_rest<1, 0, 3, true, true>(c, p1, p2, nop);
            conv_out<0>(c, qA, qB, [&] {
                bar_sync(bid, 256);
                if (elect()) {
                    const uint32_t rb = nb ^ 16;
                    mbar_expect_tx(rb, XSTG / 4);
                    asm volatile("cp.async.bulk.tensor.3d.shared::cluster.global.mbarrier::complete_tx::bytes [%0], [%1, {%3, %4, %5}], [%2];"
                                 ::"r"(rb * (XSTG / 8) + xd0), "l"(tm), "r"(rb), "r"(0), "r"(xq), "r"(yn) : "memory");
                }
            });
            CFN(6)
            conv_rest<0, 0, 3, true, true>(c, p1 + XROW, p2 + XROW, [&] { ok = mbar_test(nb, np); });
            conv_out<1>(c, qA + 2 * CGRP, qB + 2 * CGRP, nop);
            bar_arrive(bid - (BAR_EMPTY - BAR_FULL), 256);
            TLREC(3, 1 + u / 8);
            xo = (u & 24) * (XSTG / 8); qA += dq; qB += dq; dq = -dq;
            asm volatile("" : "+r"(xo));
            yn += dy2; bid ^= 1; u += 8;
            if (ok && u < 8 * (NT + 2)) continue;
            mbar_wait(nb, np);
            if (u == 8 * (NT + 2)) break;
        }
        conv_rest<1, 2, 3, true, false>(c, p1, p2, nop);
        conv_out<0>(c, qA, qB, [&] { bar_sync(BAR_EMPTY + 1, 256); });
        conv_rest<0, 3, 3, true, false>(c, p1 + XROW, p2 + XROW, nop);
        conv_out<1>(c, qA + 2 * CGRP, qB + 2 * CGRP, nop);
        bar_arrive(BAR_FULL + 1, 256);
        bar_arrive(BAR_EMPTY, 256);
        bar_arrive(BAR_EMPTY + 1, 256);
        mbar_wait(S_BAR + 8 * 2, 0);
        mbar_wait(S_BAR + 8 * 3, 0);
        if (CFT == 1 && c.sink == 0x12345) sts32(S_RED + 36, c.sink);
        TLREC(3, 35); CYS(3)
    } else {
        const int wg = warp >> 2, wq = warp & 3;
        if (warp == 0) {
            if (PRO & 1) bar_sync(0, 160);
            if (elect()) {
#pragma unroll
                for (int s = 0; s < 5; s++) mbar_init(S_WBAR + 8 * s, 1);
                asm volatile("fence.mbarrier_init.release.cluster;" ::: "memory");
#define LW1(i) { mbar_expect_tx(S_WBAR + 8 * i, WBYTES / 3); bulk_load(S_W1 + i * (WBYTES / 3), w1 + i * (WBYTES / 3), WBYTES / 3, S_WBAR + 8 * i); }
#define LW2(i) { mbar_expect_tx(S_WBAR + 24 + 8 * i, WBYTES / 2); bulk_load(S_W2 + i * (WBYTES / 2), w2 + i * (WBYTES / 2), WBYTES / 2, S_WBAR + 24 + 8 * i); }
                if (PRO & 4) { LW1(0) LW1(1) LW1(2) if (!(PRO & 2)) { LW2(0) LW2(1) } }
                else { LW2(0) LW2(1) if (!(PRO & 2)) { LW1(0) LW1(1) LW1(2) } }
                TLREC(3, 46);
            }
        }
        bar_arrive(BAR_EMPTY + wg, 256);
        if (tid < 64) sts32(S_ST + tid * 4, tid < 32 ? 0x00003f80u : 0x42c00000u);
        bar_sync(BAR_W, 256);
        uint32_t osc2;
        auto cvt_w2 = [&] {
            uint32_t r[18][4], m = 0;
#pragma unroll
            for (int h = 0; h < 2; h++) {
                mbar_wait(S_WBAR + 24 + 8 * h, 0);
                if (wg == 1) TLREC(3, 51 + h);
                if ((PRO & 6) == 2 && h == 0 && warp == 0 && elect()) { LW1(0) LW1(1) LW1(2) }
#pragma unroll
                for (int j = 0; j < 9; j++) {
                    uint32_t* q = r[h * 9 + j];
                    lds128(q, S_W2 + h * (WBYTES / 2) + (warp * 3 + j / 3) * 1536 + (lane >> 2) * 192 + (j % 3) * 64 + (lane & 3) * 16);
                    m = habsmax(habsmax(m, q[0]), habsmax(habsmax(q[1], q[2]), q[3]));
                }
            }
            m &= 0x7fff7fffu;
            m = __reduce_max_sync(0xffffffffu, max(m >> 16, m & 0xffffu));
            if (lane == 0) sts32(S_RED + warp * 4, m);
            bar_sync(BAR_W, 256);
            m = __reduce_max_sync(0xffffffffu, lds32(S_RED + (lane & 7) * 4));
            const int e = max(min(123 - (int)(m >> 7), 100), -5);
            const uint32_t chi = (0x3fc2u + ((e - 112) << 7)) * 0x10001u, clo = (0x3b51u + ((e - 112) << 7)) * 0x10001u;
            const float wsc = __uint_as_float((uint32_t)(127 + e) << 23) * INV2A;
            osc2 = ((uint32_t)(127 - e + (EPI == 1 ? 112 : 0)) << 7) * 0x10001u;
#pragma unroll
            for (int j = 0; j < 18; j++) {
#pragma unroll
                for (int k = 0; k < 4; k++)
                    r[j][k] = ((WCVT >> (k & 1)) & 1) ? b2h(bfma(r[j][k], chi, bmul(r[j][k], clo)))
                                                      : (pack_h2z(bf_lo2(r[j][k]) * wsc, bf_hi(r[j][k]) * wsc) + W2RND) & ~W2MSK;
                stsm4(S_W2 + (j / 9) * (WBYTES / 2) + (warp * 3 + j % 9 / 3) * 1536 + (j % 3) * 512 + lane * 16, r[j]);
            }
        };
        auto cvt_w1 = [&] {
            const int kr = lane & 7, nb = (kr + wg * 4 + (lane >> 3)) & 7;
#pragma unroll 1
            for (int i = 0; i < 3; i++) {
                const uint32_t base = S_W1 + (i * 4 + wq) * 6144;
                uint32_t r[6][4];
                mbar_wait(S_WBAR + 8 * i, 0);
                if (wg == 0) TLREC(3, 48 + i);
                if ((PRO & 6) == 6 && i == 0 && warp == 0 && elect()) { LW2(0) LW2(1) }
#pragma unroll
                for (int j = 0; j < 6; j++) lds128(r[j], base + kr * 768 + (j * 8 + nb) * 16);
                bar_sync(BAR_PAIR + wq, 64);
#pragma unroll
                for (int j = 0; j < 6; j++)
                    sts128(base + kr * 16 + (j * 8 + nb) * 128,
                           (WCVT & 4) ? b2h(bmul(r[j][0], 0x07800780u)) : pack_h2(bf_lo2(r[j][0]), bf_hi(r[j][0])),
                           (WCVT & 8) ? b2h(bmul(r[j][1], 0x07800780u)) : pack_h2(bf_lo2(r[j][1]), bf_hi(r[j][1])),
                           (WCVT & 4) ? b2h(bmul(r[j][2], 0x07800780u)) : pack_h2(bf_lo2(r[j][2]), bf_hi(r[j][2])),
                           (WCVT & 8) ? b2h(bmul(r[j][3], 0x07800780u)) : pack_h2(bf_lo2(r[j][3]), bf_hi(r[j][3])));
            }
        };
        if (PRO & 4) { cvt_w1(); if (wg == 1) TLREC(3, 53); cvt_w2(); }
        else { cvt_w2(); if (wg == 1) TLREC(3, 53); cvt_w1(); }
        asm volatile("fence.proxy.async.shared::cta;" ::: "memory");
        TLREC(wg, 1);
        const uint32_t cbase = S_C + wq * CGRP + (lane & 15) * CPITCH + (lane >> 4) * 16;
        const int gstep = dy * TSTEP;
        uint32_t goff = ((yb + dy * (2 + 2 * wg + (wq >> 1))) * IMG_W + w0 + (wq & 1) * 16 + (lane >> 2)) * (CH * 2) + (lane & 3) * 16;
        uint32_t H[96], a1[24], b[24], e[24], acc[24], res[24], st[2], sq[4], t[16], sink = lane;
        float sd[4];
        bool risky;
#pragma unroll
        for (int i = 0; i < 24; i++) { acc[i] = 0; res[i] = 0; }
        const uint32_t cb = cbase + wg * CBUF;
#define LDA(dst) _Pragma("unroll") for (int kk = 0; kk < 6; kk++) ldsm4(dst + 4 * kk, cb + kk * 32);
#define FETCH() { if (!LAST) { if (PEELT || i < NT / 2 - 1) bar_sync(BAR_FULL + wg, 256); LDA(b) } }
#define RELEASE() { if (!LAST) bar_arrive_wg<BAR_EMPTY>(wg); }
#define FULL() { if (!LAST) bar_sync_wg<BAR_FULL>(wg); }
#define LDB(k0, k1) if (!LAST) { _Pragma("unroll") for (int kk = k0; kk < k1; kk++) ldsm4(b + 4 * kk, cb + kk * 32); }
#define GL(p) gelu<8>(H + 8 * (p))
#define GA8(p) { if (!LAST) gelu_a<8>(t, H + 8 * (p)); }
#define GAF(p) gelu_a<8>(t, H + 8 * (p))
#define GB8(p) gelu_b<8>(H + 8 * (p), t)
#define G1(j, k0, k1) { if (!LAST || j != 0) gemm1<j, k0, k1>(H, a1, db); }
#define G1C(j, k0, k1) { if (!LAST || j != 0) { gemm1<j, k0, k1>(H, a1, db); C; } }
#define SX
#define LSP 8
#define LOA LO(0, LSP);
#define LOB LO(LSP, 24);
#define G2(k0, k1) gemm2<k0, k1>(acc, H, db)
#define P(ks, j, kk) G2(ks, ks + 1); G1(j, kk, kk + 1)
#define Q(j, kk, ks) G1(j, kk, kk + 1); G2(ks, ks + 1)
#define F wg_fence()
#define C wg_commit()
#define W(n) wg_wait<n>()
#define RDY(j) { if (!LAST || j != 0) pin<CN / 4>(H + (j) * (CN / 4)); }
#define CVT() epi_cvt(e, acc)
#define EO(r) epi_out<r>(e, res, osc2, out - gstep + goff, i > 0)
#define RES(r) load_res<r>(res, x + goff - (i > 0 ? gstep : 0))
#define RESN(r) { if (!LAST) load_res<r>(res, x + goff); }
#define GN(w0, n) gelu<n>(H + (w0))
#define GAN(w0, n) { if (!LAST) gelu_a<n>(t, H + (w0)); }
#define GBN(w0, n) gelu_b<n>(H + (w0), t)
#define LO(i0, i1) { if (!LAST) ln_out<i0, i1>(a1, b, st); }
#define S SB1
#define SMASK 0x1fbf
#define SK(k) { if ((SMASK >> (k)) & 1) SB1 }
#define LP(r) { if (!LAST) ln_part<r>(b, sq); }
#define LMC() { if (!LAST) { ln_mma(sd, sq, db); C; } }
#define RESL() { if (LAST) { load_res<0>(res, x + goff); load_res<1>(res, x + goff); } }
#define LF() { if (!LAST) risky = ln_fin(sd, st); }
#define LX2() { if (!LAST && __builtin_expect(risky, 0)) ln_fix(b, sd, st); }
        constexpr bool LAST = false;
        bar_sync(BAR_W, 256);
        TLREC(wg, 2); CYS(2)
        bar_sync(BAR_FULL + wg, 256);
        LDA(b)
        bar_arrive(BAR_EMPTY + wg, 256);
        TLREC(wg, 3); CYS(3)
        {
        constexpr uint64_t db = (uint64_t)(128 >> 4) << 32;
        LP(0); LP(1); F; LMC(); W(0); LF(); LX2() LO(0, 24);
        TLREC(wg, 4);
        F; G1(0, 0, 6); C; W(0); RDY(0); GAN(0, T0);
        }
        CYS(0)
        const uint32_t g1 = (y0 + 4 + (RB - 8) * up) * IMG_W * CH * 2, gend = (y0 + RB - 4 - (RB - 8) * up) * IMG_W * CH * 2;
#pragma unroll 1
        do {
            const int i = (goff >= g1) != (up != 0);
            F; G1(1,0,1); G1(1,1,2); G1(1,2,3); G1(1,3,4); C; CVT(); EO(0); GB8(0); GAF(1); S
            F; G1C(1,4,6); G2(0,1); G2(1,2); C; EO(1); GB8(1); GAF(2); S
            W(1); RDY(1); F; G2(2,3); G2(3,4); C; GB8(2); GAF(3); S
            FULL() LDB(0,3)
            W(1); F; G1(2,0,1); G2(4,5); G1(2,1,2); G2(5,6); G1(2,2,3); G1(2,3,4); C; GB8(3); GAF(4); S
            LDB(3,6)
            W(1); F; G1C(2,4,6); G2(6,7); G2(7,8); C; GB8(4); GAF(5); S
            W(1); RDY(2); F; G2(8,9); G2(9,10); C; LP(0); LP(1); GB8(5); GAF(6); S
            W(1); F; LMC(); G1(3,0,1); G2(10,11); G1(3,1,2); G2(11,12); G1(3,2,3); G1(3,3,4); C; GB8(6); GAF(7); S
            W(1); F; G1C(3,4,6); G2(12,13); G2(13,14); C; LF(); GB8(7); GAF(8); S
            LX2()
            W(1); RDY(3); F; G2(14,15); G2(15,16); C; LO(0,20); GB8(8); GAF(9); S
            RESL()
            W(1); F; G1(0,0,1); G2(16,17); G1(0,1,2); G2(17,18); G1(0,2,3); G1(0,3,4); C; RESN(0); LO(20,24); GB8(9); GAF(10); S
            W(1); F; G1C(0,4,6); G2(18,19); G2(19,20); C; RESN(1); GB8(10); GAF(11); S
            RELEASE()
            W(1); RDY(0); GB8(11); F; G2(20,21); G2(21,22); G2(22,23); G2(23,24); C; S GA8(0); S
            W(0); pin<24>(acc);
            goff += gstep;
        } while ((goff < gend) != (up != 0));
        CYS(1)
        {
            const int i = 1;
            constexpr bool LAST = true;
            F; G1(1,0,1); G1(1,1,2); G1(1,2,3); G1(1,3,4); C; CVT(); EO(0); GB8(0); GAF(1); S
            F; G1C(1,4,6); G2(0,1); G2(1,2); C; EO(1); GB8(1); GAF(2); S
            W(1); RDY(1); F; G2(2,3); G2(3,4); C; GB8(2); GAF(3); S
            FULL() LDB(0,3)
            W(1); F; G1(2,0,1); G2(4,5); G1(2,1,2); G2(5,6); G1(2,2,3); G1(2,3,4); C; GB8(3); GAF(4); S
            LDB(3,6)
            W(1); F; G1C(2,4,6); G2(6,7); G2(7,8); C; GB8(4); GAF(5); S
            W(1); RDY(2); F; G2(8,9); G2(9,10); C; LP(0); LP(1); GB8(5); GAF(6); S
            W(1); F; LMC(); G1(3,0,1); G2(10,11); G1(3,1,2); G2(11,12); G1(3,2,3); G1(3,3,4); C; GB8(6); GAF(7); S
            W(1); F; G1C(3,4,6); G2(12,13); G2(13,14); C; LF(); GB8(7); GAF(8); S
            LX2()
            W(1); RDY(3); F; G2(14,15); G2(15,16); C; LO(0,20); GB8(8); GAF(9); S
            RESL()
            W(1); F; G1(0,0,1); G2(16,17); G1(0,1,2); G2(17,18); G1(0,2,3); G1(0,3,4); C; RESN(0); LO(20,24); GB8(9); GAF(10); S
            W(1); F; G1C(0,4,6); G2(18,19); G2(19,20); C; RESN(1); GB8(10); GAF(11); S
            RELEASE()
            W(1); RDY(0); GB8(11); F; G2(20,21); G2(21,22); G2(22,23); G2(23,24); C; S GA8(0); S
            W(0); pin<24>(acc);
            TLREC(wg, 20);
            CVT(); epi_out<0>(e, res, osc2, out + goff, true); epi_out<1>(e, res, osc2, out + goff, true);
        }
        if (sink == 0x12345) sts32(S_RED + 36, sink);
        TLREC(wg, 77); TLRECG(wg, 79);
    }
}

typedef CUresult (*EncodeFn)(CUtensorMap*, CUtensorMapDataType, cuuint32_t, void*, const cuuint64_t*, const cuuint64_t*,
                             const cuuint32_t*, const cuuint32_t*, CUtensorMapInterleave, CUtensorMapSwizzle,
                             CUtensorMapL2promotion, CUtensorMapFloatOOBfill);

}

extern "C" void kernel_launch(void* const* d_in, const int* in_sizes, int n_in, void* d_out, int out_size) {
    static EncodeFn enc = nullptr;
    if (!enc) {
        void* fn = nullptr;
        cudaDriverEntryPointQueryResult qr;
        cudaGetDriverEntryPoint("cuTensorMapEncodeTiled", &fn, cudaEnableDefault, &qr);
        enc = (EncodeFn)fn;
        cudaFuncSetAttribute(replk_kernel, cudaFuncAttributeMaxDynamicSharedMemorySize, SMEM_BYTES);
    }
    CUtensorMap tm;
    const cuuint64_t gdim[3] = {CH, IMG_W, IMG_H};
    const cuuint64_t gstr[2] = {CH * 2, (cuuint64_t)IMG_W * CH * 2};
    const cuuint32_t box[3] = {CH, (SW + 4) / 2, 1};
    const cuuint32_t estr[3] = {1, 1, 1};
    enc(&tm, CU_TENSOR_MAP_DATA_TYPE_BFLOAT16, 3, d_in[0], gdim, gstr, box, estr, CU_TENSOR_MAP_INTERLEAVE_NONE,
        CU_TENSOR_MAP_SWIZZLE_NONE, CU_TENSOR_MAP_L2_PROMOTION_L2_256B, CU_TENSOR_MAP_FLOAT_OOB_FILL_NONE);
    replk_kernel<<<(IMG_W / SW) * (IMG_H / RB), 384, SMEM_BYTES>>>(
        tm, (const uint8_t*)d_in[0], (const uint8_t*)d_in[1], (const uint8_t*)d_in[2], (const uint8_t*)d_in[3],
        (const uint8_t*)d_in[4], (uint8_t*)d_out, (uint64_t)(128 >> 4) << 32);
}
```

```cpp
#include <cuda_runtime.h>
#include <cuda.h>
#include <stdint.h>

namespace {

#define CFENCE 0x304
#define NUP 1
#define BARP 1
#define ROT 2
#define USINK 0
#define UOP 1

constexpr int IMG_H = 512, IMG_W = 512, CH = 96, HID = 384;
constexpr int SW = 32;
constexpr int RB = 64;
constexpr int NT = RB / 2;
constexpr int NS = 4;
constexpr int PX = CH * 2;
constexpr int XROW = (SW + 4) * PX;
constexpr int XSTG = 2 * XROW;
constexpr int CPITCH = 208;
constexpr int CGRP = 16 * CPITCH + 64;
constexpr int CBUF = 4 * CGRP;
constexpr int WBYTES = CH * HID * 2;
constexpr int TSTEP = 4 * IMG_W * PX;

constexpr uint32_t SB = 1024;
constexpr uint32_t S_W1 = SB;
constexpr uint32_t S_W2 = S_W1 + WBYTES;
constexpr uint32_t S_X = S_W2 + WBYTES;
constexpr uint32_t S_C = S_X + NS * XSTG;
constexpr uint32_t S_BAR = S_C + 2 * CBUF;
constexpr uint32_t S_WBAR = S_BAR + 8 * NS;
constexpr uint32_t S_RED = S_WBAR + 8 * 6;
constexpr uint32_t S_ST = S_BAR + 256;
constexpr uint32_t S_ID = S_ST + 384;
constexpr int SMEM_BYTES = S_ID + 512 - SB;
static_assert(SMEM_BYTES <= 232448 && S_BAR % 128 == 0, "smem");

constexpr int BAR_FULL = 1, BAR_EMPTY = 4, BAR_W = 6, BAR_CV = 8, BAR_PAIR = 9;

constexpr float GA = 0.3292034911525734f;
constexpr uint32_t GK2 = 0x40d940d9u;
constexpr uint32_t INV2A_H = 0x3e13u;
constexpr uint32_t WSC2 = (uint32_t)(127 - 48) * 0x00800080u;
constexpr float LN_EPS = 1e-5f * 0x1p-96f;
constexpr float LN_OUT = GA * 0x1p-112f;

constexpr uint64_t DB = (uint64_t)(128 >> 4) << 32;
constexpr uint32_t D_W1 = (S_W1 >> 4) | ((48 * 128 >> 4) << 16);
constexpr uint32_t D_W2 = (S_W2 >> 4) | ((12 * 128 >> 4) << 16);
constexpr uint32_t D_ST = (S_ST >> 4) | ((128 >> 4) << 16);
constexpr uint32_t D_ID = (S_ID >> 4) | ((256 >> 4) << 16);

template <int SCALE_D> __device__ __forceinline__ void wg_n96_h(uint32_t* d, const uint32_t* a, uint64_t desc);
template <>
__device__ __forceinline__ void wg_n96_h<0>(uint32_t* d, const uint32_t* a, uint64_t desc) {
    asm volatile("wgmma.mma_async.sync.aligned.m64n96k16.f16.f16.f16 {"
        "%0,%1,%2,%3,%4,%5,%6,%7,%8,%9,%10,%11,%12,%13,%14,%15,"
        "%16,%17,%18,%19,%20,%21,%22,%23},"
        "{%24,%25,%26,%27}, %28, 0, 1, 1, 1;"
        : "=r"(d[0]), "=r"(d[1]), "=r"(d[2]), "=r"(d[3]), "=r"(d[4]), "=r"(d[5]), "=r"(d[6]), "=r"(d[7]),
          "=r"(d[8]), "=r"(d[9]), "=r"(d[10]), "=r"(d[11]), "=r"(d[12]), "=r"(d[13]), "=r"(d[14]), "=r"(d[15]),
          "=r"(d[16]), "=r"(d[17]), "=r"(d[18]), "=r"(d[19]), "=r"(d[20]), "=r"(d[21]), "=r"(d[22]), "=r"(d[23])
        : "r"(a[0]), "r"(a[1]), "r"(a[2]), "r"(a[3]), "l"(desc));
}
template <>
__device__ __forceinline__ void wg_n96_h<1>(uint32_t* d, const uint32_t* a, uint64_t desc) {
    asm volatile("wgmma.mma_async.sync.aligned.m64n96k16.f16.f16.f16 {"
        "%0,%1,%2,%3,%4,%5,%6,%7,%8,%9,%10,%11,%12,%13,%14,%15,"
        "%16,%17,%18,%19,%20,%21,%22,%23},"
        "{%24,%25,%26,%27}, %28, 1, 1, 1, 1;"
        : "+r"(d[0]), "+r"(d[1]), "+r"(d[2]), "+r"(d[3]), "+r"(d[4]), "+r"(d[5]), "+r"(d[6]), "+r"(d[7]),
          "+r"(d[8]), "+r"(d[9]), "+r"(d[10]), "+r"(d[11]), "+r"(d[12]), "+r"(d[13]), "+r"(d[14]), "+r"(d[15]),
          "+r"(d[16]), "+r"(d[17]), "+r"(d[18]), "+r"(d[19]), "+r"(d[20]), "+r"(d[21]), "+r"(d[22]), "+r"(d[23])
        : "r"(a[0]), "r"(a[1]), "r"(a[2]), "r"(a[3]), "l"(desc));
}

__device__ __forceinline__ void wg_fence() { asm volatile("wgmma.fence.sync.aligned;" ::: "memory"); }
__device__ __forceinline__ void wg_commit() { asm volatile("wgmma.commit_group.sync.aligned;" ::: "memory"); }
template <int N> __device__ __forceinline__ void wg_wait() { asm volatile("wgmma.wait_group.sync.aligned %0;" ::"n"(N) : "memory"); }
template <int N> __device__ __forceinline__ void pin(uint32_t* r) {
#pragma unroll
    for (int i = 0; i < N; i++) asm volatile("" : "+r"(r[i])::"memory");
}
template <int N> __device__ __forceinline__ void pin(float* r) {
#pragma unroll
    for (int i = 0; i < N; i++) asm volatile("" : "+f"(r[i])::"memory");
}
__device__ __forceinline__ void cfence(uint32_t& sink) {
    uint32_t ck;
    asm volatile("mov.u32 %0, %%clock;" : "=r"(ck)::"memory");
    sink ^= ck;
}
__device__ __forceinline__ uint64_t mkd(uint64_t db, uint32_t lo) { uint64_t d; asm volatile("add.u64 %0, %1, %2;" : "=l"(d) : "l"(db), "l"((uint64_t)lo)); return d; }

__device__ __forceinline__ void bar_sync(int id, int n) { asm volatile("bar.sync %0, %1;" ::"r"(id), "r"(n) : "memory"); }
__device__ __forceinline__ void bar_arrive(int id, int n) { asm volatile("bar.arrive %0, %1;" ::"r"(id), "r"(n) : "memory"); }
template <int ID> __device__ __forceinline__ void bar_sync_wg(int wg) {
    if (BARP & 1) asm volatile("{.reg .pred p; setp.ne.u32 p, %0, 0; @p bar.sync %2, 256; @!p bar.sync %1, 256;}" ::"r"(wg), "n"(ID), "n"(ID + 1) : "memory");
    else bar_sync(ID + wg, 256);
}
template <int ID> __device__ __forceinline__ void bar_arrive_wg(int wg) {
    if (BARP & 2) asm volatile("{.reg .pred p; setp.ne.u32 p, %0, 0; @p bar.arrive %2, 256; @!p bar.arrive %1, 256;}" ::"r"(wg), "n"(ID), "n"(ID + 1) : "memory");
    else bar_arrive(ID + wg, 256);
}
__device__ __forceinline__ void mbar_init(uint32_t a, uint32_t cnt) { asm volatile("mbarrier.init.shared::cta.b64 [%0], %1;" ::"r"(a), "r"(cnt) : "memory"); }
__device__ __forceinline__ void mbar_expect_tx(uint32_t a, uint32_t bytes) { asm volatile("mbarrier.arrive.expect_tx.shared::cta.b64 _, [%0], %1;" ::"r"(a), "r"(bytes) : "memory"); }
__device__ __forceinline__ void mbar_wait(uint32_t a, uint32_t parity) {
    asm volatile("{.reg .pred p, q; .reg .u32 g; mov.u32 g, 0;\n"
                 "L: mbarrier.try_wait.parity.shared::cta.b64 p, [%0], %1;\n"
                 "add.u32 g, g, 1; setp.lt.and.u32 q, g, 0x400000, !p; @q bra L;}" ::"r"(a), "r"(parity) : "memory");
}
__device__ __forceinline__ bool mbar_test(uint32_t a, uint32_t parity) {
    uint32_t ok;
    asm volatile("{.reg .pred p; mbarrier.test_wait.parity.shared::cta.b64 p, [%1], %2; selp.u32 %0, 1, 0, p;}" : "=r"(ok) : "r"(a), "r"(parity) : "memory");
    return ok;
}
__device__ __forceinline__ bool elect() {
    uint32_t ok;
    asm volatile("{.reg .pred p; elect.sync _|p, 0xffffffff; selp.u32 %0, 1, 0, p;}" : "=r"(ok));
    return ok;
}
__device__ __forceinline__ void tma_box(const CUtensorMap* tm, uint32_t dst, uint32_t bar, int xq, int yq) {
    mbar_expect_tx(bar, XSTG / 4);
    asm volatile("cp.async.bulk.tensor.3d.shared::cluster.global.mbarrier::complete_tx::bytes [%0], [%1, {%3, %4, %5}], [%2];"
                 ::"r"(dst), "l"(tm), "r"(bar), "r"(0), "r"(xq), "r"(yq) : "memory");
}
__device__ __forceinline__ void tma_x(const CUtensorMap* tm, int slot, int q, int xq, int yq) { tma_box(tm, S_X + slot * XSTG + q * (XSTG / 4), S_BAR + 8 * slot, xq, yq); }
__device__ __forceinline__ void bulk_load(uint32_t dst, const void* src, uint32_t bytes, uint32_t bar) {
    mbar_expect_tx(bar, bytes);
    asm volatile("cp.async.bulk.shared::cluster.global.mbarrier::complete_tx::bytes [%0], [%1], %2, [%3];"
                 ::"r"(dst), "l"(src), "r"(bytes), "r"(bar) : "memory");
}
__device__ __forceinline__ void bulk_store(void* dst, uint32_t src, uint32_t bytes) {
    asm volatile("cp.async.bulk.global.shared::cta.bulk_group [%0], [%1], %2;" ::"l"(dst), "r"(src), "r"(bytes) : "memory");
}
__device__ __forceinline__ void bulk_commit() { asm volatile("cp.async.bulk.commit_group;" ::: "memory"); }
__device__ __forceinline__ void bulk_wait() { asm volatile("cp.async.bulk.wait_group 0;" ::: "memory"); }
__device__ __forceinline__ uint32_t lds32(uint32_t a) { uint32_t v; asm volatile("ld.shared.b32 %0, [%1];" : "=r"(v) : "r"(a)); return v; }
__device__ __forceinline__ void lds128(uint32_t* r, uint32_t a) { asm volatile("ld.shared.v4.b32 {%0,%1,%2,%3}, [%4];" : "=r"(r[0]), "=r"(r[1]), "=r"(r[2]), "=r"(r[3]) : "r"(a)); }
__device__ __forceinline__ void sts32(uint32_t a, uint32_t v) { asm volatile("st.shared.b32 [%0], %1;" ::"r"(a), "r"(v)); }
__device__ __forceinline__ void sts128(uint32_t a, uint32_t x, uint32_t y, uint32_t z, uint32_t w) { asm volatile("st.shared.v4.b32 [%0], {%1,%2,%3,%4};" ::"r"(a), "r"(x), "r"(y), "r"(z), "r"(w)); }
__device__ __forceinline__ void ldsm4(uint32_t& r0, uint32_t& r1, uint32_t& r2, uint32_t& r3, uint32_t a) {
    asm volatile("ldmatrix.sync.aligned.m8n8.x4.shared.b16 {%0,%1,%2,%3}, [%4];" : "=r"(r0), "=r"(r1), "=r"(r2), "=r"(r3) : "r"(a));
}
__device__ __forceinline__ void ldsm4(uint32_t* r, uint32_t a) { ldsm4(r[0], r[1], r[2], r[3], a); }
__device__ __forceinline__ void ldsm2(uint32_t& r0, uint32_t& r1, uint32_t a) {
    asm volatile("ldmatrix.sync.aligned.m8n8.x2.shared.b16 {%0,%1}, [%2];" : "=r"(r0), "=r"(r1) : "r"(a));
}
__device__ __forceinline__ void stsm4(uint32_t a, const uint32_t* r) {
    asm volatile("stmatrix.sync.aligned.m8n8.x4.shared.b16 [%4], {%0,%1,%2,%3};" ::"r"(r[0]), "r"(r[1]), "r"(r[2]), "r"(r[3]), "r"(a));
}
__device__ __forceinline__ uint32_t bfma(uint32_t a, uint32_t b, uint32_t c) { uint32_t d; asm("fma.rn.bf16x2 %0, %1, %2, %3;" : "=r"(d) : "r"(a), "r"(b), "r"(c)); return d; }
__device__ __forceinline__ uint32_t bmul(uint32_t a, uint32_t b) { uint32_t d; asm("mul.rn.bf16x2 %0, %1, %2;" : "=r"(d) : "r"(a), "r"(b)); return d; }
__device__ __forceinline__ uint32_t badd(uint32_t a, uint32_t b) { uint32_t d; asm("add.rn.bf16x2 %0, %1, %2;" : "=r"(d) : "r"(a), "r"(b)); return d; }
__device__ __forceinline__ uint32_t vfma(uint32_t a, uint32_t b, uint32_t c) { uint32_t d; asm volatile("fma.rn.bf16x2 %0, %1, %2, %3;" : "=r"(d) : "r"(a), "r"(b), "r"(c)); return d; }
__device__ __forceinline__ void vacc(uint32_t& d, uint32_t a, uint32_t b) { asm volatile("fma.rn.bf16x2 %0, %1, %2, %0;" : "+r"(d) : "r"(a), "r"(b)); }
__device__ __forceinline__ uint32_t vadd(uint32_t a, uint32_t b) { uint32_t d; asm volatile("add.rn.bf16x2 %0, %1, %2;" : "=r"(d) : "r"(a), "r"(b)); return d; }
__device__ __forceinline__ uint32_t vsub(uint32_t a, uint32_t b) { uint32_t d; asm volatile("sub.rn.bf16x2 %0, %1, %2;" : "=r"(d) : "r"(a), "r"(b)); return d; }
__device__ __forceinline__ uint32_t vmul(uint32_t a, uint32_t b) { uint32_t d; asm volatile("mul.rn.bf16x2 %0, %1, %2;" : "=r"(d) : "r"(a), "r"(b)); return d; }
__device__ __forceinline__ uint32_t habsmax(uint32_t a, uint32_t b) { uint32_t d; asm("max.xorsign.abs.bf16x2 %0, %1, %2;" : "=r"(d) : "r"(a), "r"(b)); return d; }
__device__ __forceinline__ float bf_lo(uint32_t v) { return __uint_as_float(v << 16); }
__device__ __forceinline__ float bf_hi(uint32_t v) { return __uint_as_float(v & 0xffff0000u); }
__device__ __forceinline__ uint32_t pack_h2(float lo, float hi) { uint32_t d; asm("cvt.rn.f16x2.f32 %0, %1, %2;" : "=r"(d) : "f"(hi), "f"(lo)); return d; }
__device__ __forceinline__ uint32_t pack_b2(float lo, float hi) { uint32_t d; asm("cvt.rn.bf16x2.f32 %0, %1, %2;" : "=r"(d) : "f"(hi), "f"(lo)); return d; }
__device__ __forceinline__ uint32_t b2h(uint32_t v) { return v + 7u * (v & 0x7fff7fffu); }
__device__ __forceinline__ float rsq(float v) { float r; asm("rsqrt.approx.ftz.f32 %0, %1;" : "=f"(r) : "f"(v)); return r; }

struct Conv {
    uint32_t w[50];
    uint32_t s[20];
    uint32_t accA[4][8], accB[4][4];
    uint32_t sink;
    uint32_t xa[2][12], xb[2][8];
};
template <int S, int P, int MODE>
__device__ __forceinline__ void tap_col(uint32_t x, const uint32_t* w, uint32_t (&d)[S], const uint32_t (&src)[S]) {
#pragma unroll
    for (int j = 4; j >= 0; j--) {
        const int q = P - j;
        if (q < 0 || q >= S) continue;
        if (j > 0 || MODE == 0) vacc(d[q], x, w[2 * j]);
        else if (MODE == 1) d[q] = vmul(x, w[0]);
        else d[q] = vfma(x, w[0], src[q]);
    }
}
template <int R, int K> __device__ __forceinline__ void conv_ld(Conv& c, uint32_t a1) {
    ldsm4(c.xa[R][2 * K + 2], c.xb[R][2 * K], c.xa[R][2 * K + 3], c.xb[R][2 * K + 1], a1 + K * 2 * PX);
}
#define CFN(n) { if ((CFENCE >> n) & 1) cfence(c.sink); }
#define ALLCOLS CA(0); CA(1); CA(2); CB(0); CA(3); CB(1); CA(4); CB(2); CA(5); CB(3); CA(6); CB(4); CA(7); CB(5); CA(8); CB(6); CA(9); CB(7); CA(10); CA(11);
template <int R, typename Fn>
__device__ __forceinline__ void conv_out(Conv& c, uint32_t sA, uint32_t sB, Fn before_store) {
#define CA(p) tap_col<8, p, 0>(c.xa[R][p], c.w + 41, c.accA[R], c.accA[R])
#define CB(p) tap_col<4, p, 0>(c.xb[R][p], c.w + 40, c.accB[R], c.accB[R])
    CA(0); CA(1); CA(2); CB(0); CA(3); CB(1); CA(4); CB(2); CA(5); CB(3); CA(6); CB(4); CA(7); CB(5);
    before_store();
    stsm4(sA, c.accA[R]);
    CA(8); CB(6); CA(9); CB(7); CA(10); CA(11);
    stsm4(sB, c.accB[R]);
    stsm4(sA + 4 * CPITCH, c.accA[R] + 4);
#undef CA
#undef CB
}
template <int S, int P, int R, bool OLD, bool NEW>
__device__ __forceinline__ void diff_col(const uint32_t (&x)[2][S + 4], const uint32_t* w, uint32_t (&acc)[4][S]) {
    if (!OLD && !NEW) return;
    const uint32_t d = vsub(x[0][P], x[1][P]);
    if (R == 1) {
        if (OLD) tap_col<S, P, 0>(d, w + 20, acc[0], acc[0]);
        if (NEW) tap_col<S, P, 2>(d, w, acc[2], acc[3]);
    } else {
        if (OLD) tap_col<S, P, 0>(d, w + 30, acc[1], acc[1]);
        if (NEW) tap_col<S, P, 0>(d, w + 10, acc[3], acc[3]);
    }
}
template <int R, bool OLD, bool NEW, typename Fn>
__device__ __forceinline__ void conv_rest(Conv& c, uint32_t a1, uint32_t a2, Fn mid) {
    if (R == 1) {
        if (OLD) {
#define CA(p) tap_col<8, p, 1>(c.xa[1][p], c.s + 11, c.accA[0], c.accA[0])
#define CB(p) tap_col<4, p, 1>(c.xb[1][p], c.s + 10, c.accB[0], c.accB[0])
            ALLCOLS
#undef CA
#undef CB
#pragma unroll
            for (int q = 0; q < 8; q++) { c.accA[1][q] = vadd(c.accA[3][q], c.accA[0][q]); c.accA[0][q] = vadd(c.accA[2][q], c.accA[0][q]); }
#pragma unroll
            for (int q = 0; q < 4; q++) { c.accB[1][q] = vadd(c.accB[3][q], c.accB[0][q]); c.accB[0][q] = vadd(c.accB[2][q], c.accB[0][q]); }
            CFN(7)
        }
        if (NEW) {
#define CA(p) tap_col<8, p, 1>(c.xa[1][p], c.s + 1, c.accA[3], c.accA[3])
#define CB(p) tap_col<4, p, 1>(c.xb[1][p], c.s, c.accB[3], c.accB[3])
            ALLCOLS
#undef CA
#undef CB
            CFN(8)
        }
    }
#define CA(p) diff_col<8, p, R, OLD, NEW>(c.xa, c.w + 1, c.accA)
#define CB(p) diff_col<4, p, R, OLD, NEW>(c.xb, c.w, c.accB)
    CA(0); CA(1); CFN(0)
    ldsm2(c.xa[1 - R][0], c.xa[1 - R][1], a2);
    CA(2); CB(0); CA(3); CB(1); CFN(1)
    conv_ld<1 - R, 0>(c, a1);
    CA(4); CB(2); CA(5); CB(3); CFN(2)
    conv_ld<1 - R, 1>(c, a1);
    CA(6); CB(4); CA(7); CB(5); CFN(3)
    conv_ld<1 - R, 2>(c, a1);
    CA(8); CB(6); CA(9); CB(7); CFN(4)
    conv_ld<1 - R, 3>(c, a1);
    CA(10); CA(11); CFN(5)
    ldsm2(c.xa[1 - R][10], c.xa[1 - R][11], a2 + 10 * PX);
    mid();
    CFN(9)
#undef CA
#undef CB
}
#undef ALLCOLS

template <int J, int K0, int K1> __device__ __forceinline__ void gemm1(uint32_t* H, const uint32_t* a1, uint64_t db) {
#pragma unroll
    for (int kk = K0; kk < K1; kk++) {
        const uint64_t d = mkd(db, D_W1 + ((2 * kk * 48 + J * 12) * 128 >> 4));
        if (kk == 0) wg_n96_h<0>(H + J * 24, a1, d);
        else wg_n96_h<1>(H + J * 24, a1 + 4 * kk, d);
    }
}
template <int K0, int K1> __device__ __forceinline__ void gemm2(uint32_t* acc, const uint32_t* H, uint64_t db) {
#pragma unroll
    for (int ks = K0; ks < K1; ks++) {
        const uint64_t d = mkd(db, D_W2 + (2 * ks * 12 * 128 >> 4));
        if (ks == 0) wg_n96_h<0>(acc, H, d);
        else wg_n96_h<1>(acc, H + 4 * ks, d);
    }
}
template <int N> __device__ __forceinline__ void gelu_a(uint32_t* t, const uint32_t* h) {
#pragma unroll
    for (int i = 0; i < N; i++) {
        uint32_t p, u;
        asm("fma.rn.f16x2 %0, %1, %1, %2;" : "=r"(p) : "r"(h[i]), "r"(GK2));
        asm("mul.rn.f16x2 %0, %1, %2;" : "=r"(u) : "r"(h[i]), "r"(p));
        if (i < N - NUP) {
            uint32_t a, b;
            asm("{.reg .b16 l, h, x; mov.b32 {l, h}, %2; tanh.approx.f16 x, l; cvt.u32.u16 %0, x; tanh.approx.f16 x, h; cvt.u32.u16 %1, x;}" : "=r"(a), "=r"(b) : "r"(u));
            asm volatile("prmt.b32 %0, %1, %2, 0x5410;" : "=r"(t[i]) : "r"(a), "r"(b));
        } else asm("tanh.approx.f16x2 %0, %1;" : "=r"(t[i]) : "r"(u));
    }
    pin<N>(t);
}
template <int N> __device__ __forceinline__ void gelu_b(uint32_t* h, const uint32_t* t) {
#pragma unroll
    for (int i = 0; i < N; i++) asm volatile("fma.rn.f16x2 %0, %1, %2, %1;" : "=r"(h[i]) : "r"(h[i]), "r"(t[i]));
}
template <int r> __device__ __forceinline__ void ln_part(const uint32_t* a, uint32_t* sq) {
    uint32_t s[6], q[2];
#pragma unroll
    for (int i = 0; i < 6; i++) s[i] = badd(a[4 * i + r], a[4 * i + 2 + r]);
    sq[r] = badd(badd(badd(s[0], s[1]), badd(s[2], s[3])), badd(s[4], s[5]));
#pragma unroll
    for (int i = 0; i < 12; i++) q[i & 1] = (i < 2) ? bmul(a[2 * i + r], a[2 * i + r]) : bfma(a[2 * i + r], a[2 * i + r], q[i & 1]);
    sq[2 + r] = badd(q[0], q[1]);
    pin<1>(sq + r); pin<1>(sq + 2 + r);
}
__device__ __forceinline__ void ln_mma(float* d, const uint32_t* sq, uint64_t db) {
    asm volatile("wgmma.mma_async.sync.aligned.m64n8k16.f32.bf16.bf16 {%0,%1,%2,%3}, {%4,%5,%6,%7}, %8, 0, 1, 1, 1;"
                 : "=f"(d[0]), "=f"(d[1]), "=f"(d[2]), "=f"(d[3]) : "r"(sq[0]), "r"(sq[1]), "r"(sq[2]), "r"(sq[3]), "l"(mkd(db, D_ST)));
}
__device__ __forceinline__ bool ln_fin(float* d, uint32_t* st) {
    pin<4>(d);
    bool risky = false;
#pragma unroll
    for (int r = 0; r < 2; r++) {
        const float q = rsq(fmaf(-d[2 * r], d[2 * r], d[2 * r + 1] + LN_EPS * (CH * CH)));
        const float z = d[2 * r] * q;
        risky |= !(fabsf(z) <= 1.f);
        st[r] = pack_b2(q * (LN_OUT * CH), z * -LN_OUT);
    }
    pin<2>(st);
    return __any_sync(0xffffffffu, risky);
}
__device__ __forceinline__ void ln_fix(uint32_t* a, const float* d, uint32_t* st) {
#pragma unroll
    for (int r = 0; r < 2; r++) {
        const uint32_t m2 = pack_b2(d[2 * r] * (-1.f / CH), d[2 * r] * (-1.f / CH));
        uint32_t q[2];
#pragma unroll
        for (int i = 0; i < 12; i++) {
            a[2 * i + r] = badd(a[2 * i + r], m2);
            q[i & 1] = (i < 2) ? bmul(a[2 * i + r], a[2 * i + r]) : bfma(a[2 * i + r], a[2 * i + r], q[i & 1]);
        }
        const uint32_t qq = badd(q[0], q[1]);
        float v = bf_lo(qq) + bf_hi(qq);
        v += __shfl_xor_sync(0xffffffffu, v, 1);
        v += __shfl_xor_sync(0xffffffffu, v, 2);
        st[r] = pack_b2(rsq(fmaf(v, 1.f / CH, LN_EPS)) * LN_OUT, 0.f);
    }
}
template <int I0, int I1> __device__ __forceinline__ void ln_out(uint32_t* a, const uint32_t* b, const uint32_t* st) {
#pragma unroll
    for (int i = I0; i < I1; i++) {
        uint32_t v;
        asm("{.reg .b16 l, h; .reg .b32 ll, hh; mov.b32 {l, h}, %2; mov.b32 ll, {l, l}; mov.b32 hh, {h, h}; fma.rn.bf16x2 %0, %1, ll, hh;}"
            : "=r"(v) : "r"(b[i]), "r"(st[i & 1]));
        a[i] = b2h(v);
        pin<1>(a + i);
    }
}
template <int J0, int J1> __device__ __forceinline__ void epi_mma(float* d, const uint32_t* acc, uint64_t db) {
    const uint64_t ds = mkd(db, D_ID);
#pragma unroll
    for (int j = J0; j < J1; j++)
        asm volatile("wgmma.mma_async.sync.aligned.m64n16k16.f32.f16.f16 {%0,%1,%2,%3,%4,%5,%6,%7}, {%8,%9,%10,%11}, %12, 0, 1, 1, 1;"
                     : "=f"(d[8 * j]), "=f"(d[8 * j + 1]), "=f"(d[8 * j + 2]), "=f"(d[8 * j + 3]), "=f"(d[8 * j + 4]), "=f"(d[8 * j + 5]), "=f"(d[8 * j + 6]), "=f"(d[8 * j + 7])
                     : "r"(acc[4 * j]), "r"(acc[4 * j + 1]), "r"(acc[4 * j + 2]), "r"(acc[4 * j + 3]), "l"(ds));
}
template <int I> __device__ __forceinline__ void epi_red(const float* d, uint8_t* gp) {
#pragma unroll
    for (int r = 0; r < 2; r++) {
        uint32_t o[4];
#pragma unroll
        for (int jj = 0; jj < 4; jj++) o[jj] = pack_b2(d[16 * I + 4 * jj + 2 * r], d[16 * I + 4 * jj + 2 * r + 1]);
        asm volatile("red.global.add.noftz.v4.bf16x2 [%0], {%1,%2,%3,%4};" ::"l"(gp + r * 8 * PX + I * 64), "r"(o[0]), "r"(o[1]), "r"(o[2]), "r"(o[3]));
    }
}

struct Mlp {
    uint32_t H[96], a1[24], b[24], acc[24], st[2], sq[4], t[8], sink;
    float sd[4], dd[48];
};
template <bool FIRST, bool LAST>
__device__ __forceinline__ void mlp_tile(Mlp& m, const uint64_t db, const int wg, const uint32_t cb, uint8_t* op) {
    bool risky;
#define F wg_fence()
#define C wg_commit()
#define W(n) wg_wait<n>()
#define S cfence(m.sink);
#define FULL() { if (!LAST) bar_sync_wg<BAR_FULL>(wg); }
#define RELEASE() { if (!LAST) bar_arrive_wg<BAR_EMPTY>(wg); }
#define LDB(k0, k1) if (!LAST) { _Pragma("unroll") for (int kk = k0; kk < k1; kk++) ldsm4(m.b + 4 * kk, cb + kk * 32); }
#define GA8(p) { if (!LAST) gelu_a<8>(m.t, m.H + 8 * (p)); }
#define GAF(p) gelu_a<8>(m.t, m.H + 8 * (p))
#define GB8(p) gelu_b<8>(m.H + 8 * (p), m.t)
#define G1(j, k0, k1) { if (!LAST || j != 0) gemm1<j, k0, k1>(m.H, m.a1, db); }
#define G1C(j, k0, k1) { if (!LAST || j != 0) { gemm1<j, k0, k1>(m.H, m.a1, db); C; } }
#define G2(k0, k1) gemm2<k0, k1>(m.acc, m.H, db)
#define RDY(j) { if (!LAST || j != 0) pin<24>(m.H + (j) * 24); }
#define IDM(j0, j1) { if (!FIRST) epi_mma<j0, j1>(m.dd, m.acc, db); }
#define IDMC(j0, j1) { if (!FIRST) { epi_mma<j0, j1>(m.dd, m.acc, db); C; } }
#define IDR(j0, j1) { if (!FIRST) pin<8 * (j1 - j0)>(m.dd + 8 * j0); }
#define ER(k) { if (!FIRST) epi_red<k>(m.dd, op); }
#define LP(r) { if (!LAST) ln_part<r>(m.b, m.sq); }
#define LMC() { if (!LAST) { ln_mma(m.sd, m.sq, db); C; } }
#define LF() { if (!LAST) risky = ln_fin(m.sd, m.st); }
#define LX2() { if (!LAST && __builtin_expect(risky, 0)) ln_fix(m.b, m.sd, m.st); }
#define LO(i0, i1) { if (!LAST) ln_out<i0, i1>(m.a1, m.b, m.st); }
    F; IDMC(0,2); G1(1,0,1); G1(1,1,2); G1(1,2,3); C; GB8(0); GAF(1); S
    W(1); IDR(0,2); ER(0); S F; IDM(2,6); G1(1,3,4); G1(1,4,5); G1(1,5,6); C; GB8(1); GAF(2); S
    W(0); RDY(1); IDR(2,6); F; G2(0,1); G2(1,2); G2(2,3); G2(3,4); C; ER(1); GB8(2); GAF(3); S
    FULL() LDB(0,2)
    W(1); F; G1(2,0,1); G2(4,5); G1(2,1,2); G2(5,6); G1(2,2,3); G1(2,3,4); C; ER(2); GB8(3); GAF(4); S
    LDB(2,4)
    W(1); F; G1C(2,4,6); G2(6,7); G2(7,8); C; GB8(4); GAF(5); S
    LDB(4,6)
    W(1); RDY(2); F; G2(8,9); G2(9,10); C; LP(0); LP(1); GB8(5); GAF(6); S
    W(1); F; LMC(); G1(3,0,1); G2(10,11); G1(3,1,2); G2(11,12); G1(3,2,3); G1(3,3,4); C; GB8(6); GAF(7); S
    W(1); F; G1C(3,4,6); G2(12,13); G2(13,14); C; LF(); GB8(7); GAF(8); S
    LX2()
    W(1); RDY(3); F; G2(14,15); G2(15,16); C; LO(0,16); GB8(8); GAF(9); S
    W(1); F; G1(0,0,1); G2(16,17); G1(0,1,2); G2(17,18); G1(0,2,3); G1(0,3,4); C; LO(16,24); GB8(9); GAF(10); S
    RELEASE()
    W(1); F; G1C(0,4,6); G2(18,19); G2(19,20); C; GB8(10); GAF(11); S
    W(1); RDY(0); GB8(11); F; G2(20,21); G2(21,22); G2(22,23); G2(23,24); C; S GA8(0); S
    W(0);
    pin<24>(m.acc);
#undef F
#undef C
#undef W
#undef S
#undef FULL
#undef RELEASE
#undef LDB
#undef GA8
#undef GAF
#undef GB8
#undef G1
#undef G1C
#undef G2
#undef RDY
#undef IDM
#undef IDMC
#undef IDR
#undef ER
#undef LP
#undef LMC
#undef LF
#undef LX2
#undef LO
}

__global__ void __launch_bounds__(384, 1)
replk_kernel(const __grid_constant__ CUtensorMap tmx, const uint8_t* __restrict__ dwl, const uint8_t* __restrict__ dws,
             const uint8_t* __restrict__ w1, const uint8_t* __restrict__ w2, uint8_t* __restrict__ out, const uint64_t db,
             unsigned long long* __restrict__ dbg) {
    extern __shared__ __align__(1024) uint8_t smem[];
    const int tid = (threadIdx.x + ROT * 128) % 384, lane = tid & 31;
    const int warp = __shfl_sync(0xffffffffu, tid >> 5, 0);
    const int w0 = (blockIdx.x % (IMG_W / SW)) * SW, y0 = (blockIdx.x / (IMG_W / SW)) * RB;
    const int up = 1 & ~(blockIdx.x / (IMG_W / SW));
    const int dy = 1 - 2 * up, yb = y0 - 2 + (RB + 3) * up;
    if (tid == 0) sts32(S_RED + 40, (uint32_t)clock64());

    if (warp >= 8) {
        const int cw = warp - 8;
        const int tj = min((tid - 256) / 24, 4), tc = (tid - 256) % 24;
        uint2 ts[5], tl[3];
#pragma unroll
        for (int i = 0; i < 5; i++) ts[i] = __ldg(reinterpret_cast<const uint2*>(dws) + ((2 + dy * (i - 2)) * 5 + tj) * 24 + tc);
#pragma unroll
        for (int i = 0; i < 3; i++) tl[i] = __ldg(reinterpret_cast<const uint2*>(dwl) + ((1 + dy * (i - 1)) * 3 + (tj + 2) % 3) * 24 + tc);
        if (cw == 0 && elect()) {
            if ((uint32_t)__cvta_generic_to_shared(smem) != SB) __trap();
#pragma unroll
            for (int s = 0; s < NS; s++) mbar_init(S_BAR + 8 * s, 4);
            asm volatile("fence.mbarrier_init.release.cluster;" ::: "memory");
#pragma unroll
            for (int q = 0; q < 4; q++) tma_x(&tmx, 0, q, w0 - 2 + (q & 1) * 18, yb + dy * (q >> 1));
        }
        bar_sync(BAR_CV, 128);
        const int xq = w0 - 2 + (cw & 1) * 18, yq = yb + dy * (cw >> 1);
        if (elect()) tma_x(&tmx, 1, cw, xq, yq + 2 * dy);
        Conv c;
        {
            const uint32_t lm = (tj & 3) ? ~0u : 0u;
            uint32_t v[7][2];
#pragma unroll
            for (int i = 0; i < 5; i++) {
                v[i][0] = ts[i].x; v[i][1] = ts[i].y;
                if (i >= 1 && i <= 3) { v[i][0] = badd(v[i][0], tl[i - 1].x & lm); v[i][1] = badd(v[i][1], tl[i - 1].y & lm); }
                v[i][0] = bmul(v[i][0], WSC2); v[i][1] = bmul(v[i][1], WSC2);
            }
#pragma unroll
            for (int u = 0; u < 2; u++) { v[5][u] = badd(v[0][u], v[1][u]); v[6][u] = badd(v[2][u], v[3][u]); }
#pragma unroll
            for (int i = 0; i < 7; i++)
                asm volatile("st.shared.v2.b32 [%0], {%1, %2};" ::"r"(S_C + ((i * 5 + tj) * 24 + tc) * 8), "r"(v[i][0]), "r"(v[i][1]) : "memory");
            bar_sync(BAR_CV, 128);
            if (elect()) tma_x(&tmx, 2, cw, xq, yq + 4 * dy);
            const int qd = lane & 7, u = (lane >> 3) & 1;
            const uint32_t ws = S_C + ((cw < 2 + u) ? qd : 8 + (qd & 3)) * 16;
#pragma unroll
            for (int k = 0; k < 12; k++) ldsm4(c.w + 4 * k, ws + ((lane >> 4) + 2 * k) * PX);
            ldsm2(c.w[48], c.w[49], ws + 24 * PX);
#pragma unroll
            for (int k = 0; k < 5; k++) ldsm4(c.s + 4 * k, ws + ((lane >> 4) + 25 + 2 * k) * PX);
        }
        const int mi = lane >> 3, qd = lane & 7;
        const int chA = (cw < 3) ? qd : 8 + (qd & 3), pxA = (cw < 3) ? 8 * cw : 16 * (qd >> 2);
        const int chB = (cw < 2) ? qd : 8 + (qd & 3), pxB = (cw < 2) ? 24 + 4 * cw : 16 * (qd >> 2) + 8 + 4 * (cw - 2);
        const uint32_t a1 = S_X + ((mi & 1) ? (pxB + (mi >> 1)) * PX + chB * 16 : (pxA + 2 + (mi >> 1)) * PX + chA * 16);
        const uint32_t a2 = S_X + (pxA + (mi & 1)) * PX + chA * 16;
        uint32_t qA = S_C + (pxA >> 4) * CGRP + ((pxA & 15) + mi) * CPITCH + chA * 16;
        uint32_t qB = S_C + (pxB >> 4) * CGRP + ((pxB & 15) + mi) * CPITCH + chB * 16;
        auto nop = [] {};
        c.sink = lane;
        mbar_wait(S_BAR, 0);
        ldsm2(c.xa[0][0], c.xa[0][1], a2);
        conv_ld<0, 0>(c, a1); conv_ld<0, 1>(c, a1); conv_ld<0, 2>(c, a1); conv_ld<0, 3>(c, a1);
        ldsm2(c.xa[0][10], c.xa[0][11], a2 + 10 * PX);
        conv_rest<0, false, false>(c, a1 + XROW, a2 + XROW, nop);
        if (elect()) tma_x(&tmx, 3, cw, xq, yq + 6 * dy);
        mbar_wait(S_BAR + 8, 0);
        const uint32_t xs0 = S_X + (cw >> 1) * XROW + (2 + 16 * (cw & 1)) * PX;
        uint8_t* op = out + (size_t)((yq + 2 * dy) * IMG_W + w0 + 16 * (cw & 1)) * PX;
        const int64_t ostep = 2 * dy * IMG_W * PX;
        if (elect()) bulk_store(op, xs0 + XSTG, 16 * PX);
        bulk_commit();
        conv_rest<1, false, true>(c, a1 + XSTG, a2 + XSTG, nop);
        conv_rest<0, false, true>(c, a1 + XSTG + XROW, a2 + XSTG + XROW, nop);
        bar_sync(BAR_CV, 128);
        if (elect()) tma_x(&tmx, 0, cw, xq, yq + 8 * dy);
        mbar_wait(S_BAR + 16, 0);
        uint32_t u;
        asm volatile("mov.u32 %0, 24;" : "=r"(u));
        const uint32_t xd0 = S_X + cw * (XSTG / 4) - S_BAR * (XSTG / 8);
        uint32_t xo = 2 * XSTG, bid = BAR_EMPTY;
        int dq = CBUF, yn = yq + 10 * dy;
#pragma unroll 1
        for (;;) {
            const uint32_t nb = S_BAR | (u & 24), np = u >> 5;
            bool ok;
            conv_rest<1, true, true>(c, a1 + xo, a2 + xo, nop);
            conv_out<0>(c, qA, qB, [&] {
                bulk_wait();
                op += ostep;
                bar_sync(bid, 256);
                if (elect()) {
                    tma_box(&tmx, (nb ^ 16) * (XSTG / 8) + xd0, nb ^ 16, xq, u < 8 * NT ? yn : -8);
                    bulk_store(op, xs0 + xo, 16 * PX);
                }
                bulk_commit();
            });
            CFN(6)
            conv_rest<0, true, true>(c, a1 + xo + XROW, a2 + xo + XROW, [&] { ok = mbar_test(nb, np); });
            conv_out<1>(c, qA + 2 * CGRP, qB + 2 * CGRP, nop);
            bar_arrive(bid - (BAR_EMPTY - BAR_FULL), 256);
            xo = (u & 24) * (XSTG / 8); qA += dq; qB += dq; dq = -dq;
            asm volatile("" : "+r"(xo));
            yn += 2 * dy; bid ^= 1; u += 8;
            if (ok && u < 8 * (NT + 2)) continue;
            mbar_wait(nb, np);
            if (u == 8 * (NT + 2)) break;
        }
        conv_rest<1, true, false>(c, a1 + xo, a2 + xo, nop);
        conv_out<0>(c, qA, qB, [&] { bulk_wait(); bar_sync(BAR_EMPTY + 1, 256); });
        conv_rest<0, true, false>(c, a1 + xo + XROW, a2 + xo + XROW, nop);
        conv_out<1>(c, qA + 2 * CGRP, qB + 2 * CGRP, nop);
        bar_arrive(BAR_FULL + 1, 256);
        bar_arrive(BAR_EMPTY, 256);
        bar_arrive(BAR_EMPTY + 1, 256);
        mbar_wait(S_BAR + 8 * 2, 0);
        mbar_wait(S_BAR + 8 * 3, 0);
        if (dbg) sts32(S_RED + 36, c.sink);
    } else {
        const int wg = warp >> 2, wq = warp & 3;
        if (warp == 0 && elect()) {
#pragma unroll
            for (int s = 0; s < 5; s++) mbar_init(S_WBAR + 8 * s, 1);
            asm volatile("fence.mbarrier_init.release.cluster;" ::: "memory");
#pragma unroll
            for (int i = 0; i < 2; i++) bulk_load(S_W2 + i * (WBYTES / 2), w2 + i * (WBYTES / 2), WBYTES / 2, S_WBAR + 24 + 8 * i);
        }
        bar_arrive(BAR_EMPTY + wg, 256);
        if (tid < 64) sts32(S_ST + tid * 4, tid < 32 ? 0x00003f80u : 0x42c00000u);
        bar_sync(BAR_W, 256);
        {
            uint32_t r[18][4], mx = 0;
#pragma unroll
            for (int h = 0; h < 2; h++) {
                mbar_wait(S_WBAR + 24 + 8 * h, 0);
                if (h == 0 && warp == 0 && elect()) {
#pragma unroll
                    for (int i = 0; i < 3; i++) bulk_load(S_W1 + i * (WBYTES / 3), w1 + i * (WBYTES / 3), WBYTES / 3, S_WBAR + 8 * i);
                }
#pragma unroll
                for (int j = 0; j < 9; j++) {
                    uint32_t* q = r[h * 9 + j];
                    lds128(q, S_W2 + h * (WBYTES / 2) + (warp * 3 + j / 3) * 1536 + (lane >> 2) * PX + (j % 3) * 64 + (lane & 3) * 16);
                    mx = habsmax(habsmax(mx, q[0]), habsmax(habsmax(q[1], q[2]), q[3]));
                }
            }
            mx &= 0x7fff7fffu;
            mx = __reduce_max_sync(0xffffffffu, max(mx >> 16, mx & 0xffffu));
            if (lane == 0) sts32(S_RED + warp * 4, mx);
            bar_sync(BAR_W, 256);
            mx = __reduce_max_sync(0xffffffffu, lds32(S_RED + (lane & 7) * 4));
            const int e = max(min(123 - (int)(mx >> 7), 14), -14);
            const uint32_t wsc2 = (uint32_t)(15 + e) * 0x00800080u;
            if (tid < 128) {
                const int cm = tid >> 5, k = (tid >> 2) & 7, q = tid & 3;
                const uint32_t cv = INV2A_H - (e << 10);
                sts32(S_ID + tid * 4, (cm == 0 || cm == 3) && (k >> 1) == q ? cv << (16 * (k & 1)) : 0u);
            }
#pragma unroll
            for (int j = 0; j < 18; j++) {
#pragma unroll
                for (int k = 0; k < 4; k++) r[j][k] = b2h(bmul(r[j][k], wsc2));
                stsm4(S_W2 + (j / 9) * (WBYTES / 2) + (warp * 3 + j % 9 / 3) * 1536 + (j % 3) * 512 + lane * 16, r[j]);
            }
        }
        {
            const int kr = lane & 7, nb = (kr + wg * 4 + (lane >> 3)) & 7;
#pragma unroll 1
            for (int i = 0; i < 3; i++) {
                const uint32_t base = S_W1 + (i * 4 + wq) * 6144;
                uint32_t r[6][4];
                mbar_wait(S_WBAR + 8 * i, 0);
#pragma unroll
                for (int j = 0; j < 6; j++) lds128(r[j], base + kr * 768 + (j * 8 + nb) * 16);
                bar_sync(BAR_PAIR + wq, 64);
#pragma unroll
                for (int j = 0; j < 6; j++)
                    sts128(base + kr * 16 + (j * 8 + nb) * 128, pack_h2(bf_lo(r[j][0]), bf_hi(r[j][0])), pack_h2(bf_lo(r[j][1]), bf_hi(r[j][1])),
                           pack_h2(bf_lo(r[j][2]), bf_hi(r[j][2])), pack_h2(bf_lo(r[j][3]), bf_hi(r[j][3])));
            }
        }
        asm volatile("fence.proxy.async.shared::cta;" ::: "memory");
        const uint32_t cb = S_C + wg * CBUF + wq * CGRP + (lane & 15) * CPITCH + (lane >> 4) * 16;
        const uint32_t goff = ((yb + dy * (2 + 2 * wg + (wq >> 1))) * IMG_W + w0 + (wq & 1) * 16 + (lane >> 2)) * PX + (lane & 3) * 16;
        const int64_t gstep = dy * TSTEP;
        uint8_t* op = UOP ? out : out + goff;
        Mlp m;
        m.sink = lane;
        if (USINK) asm volatile("mov.u32 %0, 0;" : "=r"(m.sink));
        bar_sync(BAR_W, 256);
        bar_sync(BAR_FULL + wg, 256);
#pragma unroll
        for (int kk = 0; kk < 6; kk++) ldsm4(m.b + 4 * kk, cb + kk * 32);
        bar_arrive(BAR_EMPTY + wg, 256);
        ln_part<0>(m.b, m.sq); ln_part<1>(m.b, m.sq);
        wg_fence(); ln_mma(m.sd, m.sq, DB); wg_commit(); wg_wait<0>();
        if (ln_fin(m.sd, m.st)) ln_fix(m.b, m.sd, m.st);
        ln_out<0, 24>(m.a1, m.b, m.st);
        wg_fence(); gemm1<0, 0, 6>(m.H, m.a1, DB); wg_commit(); wg_wait<0>();
        pin<24>(m.H);
        gelu_a<8>(m.t, m.H);
        mlp_tile<true, false>(m, DB, wg, cb, nullptr);
        int i;
        asm volatile("mov.u32 %0, 1;" : "=r"(i));
#pragma unroll 1
        do {
            mlp_tile<false, false>(m, db, wg, cb, UOP ? op + goff : op);
            op += gstep;
            if (UOP) asm volatile("" : "+l"(op));
        } while (++i < NT / 2 - 1);
        if (UOP) op += goff;
        mlp_tile<false, true>(m, db, wg, cb, op);
        op += gstep;
        wg_fence(); epi_mma<0, 6>(m.dd, m.acc, db); wg_commit(); wg_wait<0>();
        pin<48>(m.dd);
        epi_red<0>(m.dd, op); epi_red<1>(m.dd, op); epi_red<2>(m.dd, op);
        if (dbg) {
            sts32(S_RED + 36, m.sink);
            uint32_t tx;
            asm volatile("mov.u32 %0, %%tid.x;" : "=r"(tx));
            if ((tx & 127) == 0) atomicAdd(dbg + (tx >> 7), (unsigned long long)((uint32_t)clock64() - lds32(S_RED + 40)));
        }
    }
}
#undef CFN

typedef CUresult (*EncodeFn)(CUtensorMap*, CUtensorMapDataType, cuuint32_t, void*, const cuuint64_t*, const cuuint64_t*,
                             const cuuint32_t*, const cuuint32_t*, CUtensorMapInterleave, CUtensorMapSwizzle,
                             CUtensorMapL2promotion, CUtensorMapFloatOOBfill);

}

#define DBG_PTR nullptr
extern "C" void kernel_launch(void* const* d_in, const int* in_sizes, int n_in, void* d_out, int out_size) {
    static EncodeFn enc = nullptr;
    if (!enc) {
        void* fn = nullptr;
        cudaDriverEntryPointQueryResult qr;
        cudaGetDriverEntryPoint("cuTensorMapEncodeTiled", &fn, cudaEnableDefault, &qr);
        enc = (EncodeFn)fn;
        cudaFuncSetAttribute(replk_kernel, cudaFuncAttributeMaxDynamicSharedMemorySize, SMEM_BYTES);
    }
    CUtensorMap tm;
    const cuuint64_t gdim[3] = {CH, IMG_W, IMG_H};
    const cuuint64_t gstr[2] = {PX, (cuuint64_t)IMG_W * PX};
    const cuuint32_t box[3] = {CH, (SW + 4) / 2, 1};
    const cuuint32_t estr[3] = {1, 1, 1};
    enc(&tm, CU_TENSOR_MAP_DATA_TYPE_BFLOAT16, 3, d_in[0], gdim, gstr, box, estr, CU_TENSOR_MAP_INTERLEAVE_NONE,
        CU_TENSOR_MAP_SWIZZLE_NONE, CU_TENSOR_MAP_L2_PROMOTION_L2_256B, CU_TENSOR_MAP_FLOAT_OOB_FILL_NONE);
    replk_kernel<<<(IMG_W / SW) * (IMG_H / RB), 384, SMEM_BYTES>>>(
        tm, (const uint8_t*)d_in[1], (const uint8_t*)d_in[2], (const uint8_t*)d_in[3], (const uint8_t*)d_in[4], (uint8_t*)d_out, DB, DBG_PTR);
}
```

```cpp
#include <cuda_runtime.h>
#include <cuda.h>
#include <stdint.h>

namespace {

#define CFENCE 0x314
#define NUP 1
#define BARP 2
#define ROT 2

constexpr int IMG_H = 512, IMG_W = 512, CH = 96, HID = 384;
constexpr int SW = 32;
constexpr int RB = 64;
constexpr int NT = RB / 2;
constexpr int NS = 4;
constexpr int PX = CH * 2;
constexpr int XROW = (SW + 4) * PX;
constexpr int XSTG = 2 * XROW;
constexpr int CPITCH = 208;
constexpr int CGRP = 16 * CPITCH + 64;
constexpr int CBUF = 4 * CGRP;
constexpr int WBYTES = CH * HID * 2;
constexpr int TSTEP = 4 * IMG_W * PX;

constexpr uint32_t SB = 1024;
constexpr uint32_t S_W1 = SB;
constexpr uint32_t S_W2 = S_W1 + WBYTES;
constexpr uint32_t S_X = S_W2 + WBYTES;
constexpr uint32_t S_C = S_X + NS * XSTG;
constexpr uint32_t S_BAR = S_C + 2 * CBUF;
constexpr uint32_t S_WBAR = S_BAR + 8 * NS;
constexpr uint32_t S_RED = S_WBAR + 8 * 6;
constexpr uint32_t S_ST = S_BAR + 256;
constexpr uint32_t S_ID = S_ST + 384;
constexpr int SMEM_BYTES = S_ID + 512 - SB;
static_assert(SMEM_BYTES <= 232448 && S_BAR % 128 == 0, "smem");

constexpr int BAR_FULL = 1, BAR_EMPTY = 4, BAR_W = 6, BAR_CV = 8, BAR_PAIR = 9;

constexpr float GA = 0.3292034911525734f;
constexpr uint32_t GK2 = 0x40d940d9u;
constexpr uint32_t INV2A_H = 0x3e13u;
constexpr uint32_t WSC2 = (uint32_t)(127 - 48) * 0x00800080u;
constexpr float LN_EPS = 1e-5f * 0x1p-96f;
constexpr float LN_OUT = GA * 0x1p-112f;

constexpr uint64_t DB = (uint64_t)(128 >> 4) << 32;
constexpr uint32_t D_W1 = (S_W1 >> 4) | ((48 * 128 >> 4) << 16);
constexpr uint32_t D_W2 = (S_W2 >> 4) | ((12 * 128 >> 4) << 16);
constexpr uint32_t D_ST = (S_ST >> 4) | ((128 >> 4) << 16);
constexpr uint32_t D_ID = (S_ID >> 4) | ((256 >> 4) << 16);

template <int SCALE_D> __device__ __forceinline__ void wg_n96_h(uint32_t* d, const uint32_t* a, uint64_t desc);
template <>
__device__ __forceinline__ void wg_n96_h<0>(uint32_t* d, const uint32_t* a, uint64_t desc) {
    asm volatile("wgmma.mma_async.sync.aligned.m64n96k16.f16.f16.f16 {"
        "%0,%1,%2,%3,%4,%5,%6,%7,%8,%9,%10,%11,%12,%13,%14,%15,"
        "%16,%17,%18,%19,%20,%21,%22,%23},"
        "{%24,%25,%26,%27}, %28, 0, 1, 1, 1;"
        : "=r"(d[0]), "=r"(d[1]), "=r"(d[2]), "=r"(d[3]), "=r"(d[4]), "=r"(d[5]), "=r"(d[6]), "=r"(d[7]),
          "=r"(d[8]), "=r"(d[9]), "=r"(d[10]), "=r"(d[11]), "=r"(d[12]), "=r"(d[13]), "=r"(d[14]), "=r"(d[15]),
          "=r"(d[16]), "=r"(d[17]), "=r"(d[18]), "=r"(d[19]), "=r"(d[20]), "=r"(d[21]), "=r"(d[22]), "=r"(d[23])
        : "r"(a[0]), "r"(a[1]), "r"(a[2]), "r"(a[3]), "l"(desc));
}
template <>
__device__ __forceinline__ void wg_n96_h<1>(uint32_t* d, const uint32_t* a, uint64_t desc) {
    asm volatile("wgmma.mma_async.sync.aligned.m64n96k16.f16.f16.f16 {"
        "%0,%1,%2,%3,%4,%5,%6,%7,%8,%9,%10,%11,%12,%13,%14,%15,"
        "%16,%17,%18,%19,%20,%21,%22,%23},"
        "{%24,%25,%26,%27}, %28, 1, 1, 1, 1;"
        : "+r"(d[0]), "+r"(d[1]), "+r"(d[2]), "+r"(d[3]), "+r"(d[4]), "+r"(d[5]), "+r"(d[6]), "+r"(d[7]),
          "+r"(d[8]), "+r"(d[9]), "+r"(d[10]), "+r"(d[11]), "+r"(d[12]), "+r"(d[13]), "+r"(d[14]), "+r"(d[15]),
          "+r"(d[16]), "+r"(d[17]), "+r"(d[18]), "+r"(d[19]), "+r"(d[20]), "+r"(d[21]), "+r"(d[22]), "+r"(d[23])
        : "r"(a[0]), "r"(a[1]), "r"(a[2]), "r"(a[3]), "l"(desc));
}

__device__ __forceinline__ void wg_fence() { asm volatile("wgmma.fence.sync.aligned;" ::: "memory"); }
__device__ __forceinline__ void wg_commit() { asm volatile("wgmma.commit_group.sync.aligned;" ::: "memory"); }
template <int N> __device__ __forceinline__ void wg_wait() { asm volatile("wgmma.wait_group.sync.aligned %0;" ::"n"(N) : "memory"); }
template <int N> __device__ __forceinline__ void pin(uint32_t* r) {
#pragma unroll
    for (int i = 0; i < N; i++) asm volatile("" : "+r"(r[i])::"memory");
}
template <int N> __device__ __forceinline__ void pin(float* r) {
#pragma unroll
    for (int i = 0; i < N; i++) asm volatile("" : "+f"(r[i])::"memory");
}
__device__ __forceinline__ void cfence(uint32_t& sink, bool on) {
    asm volatile("{.reg .pred p; setp.ne.u32 p, %1, 0; @p mov.u32 %0, %%clock;}" : "+r"(sink) : "r"((uint32_t)on) : "memory");
}
__device__ __forceinline__ uint64_t mkd(uint64_t db, uint32_t lo) { uint64_t d; asm volatile("add.u64 %0, %1, %2;" : "=l"(d) : "l"(db), "l"((uint64_t)lo)); return d; }

__device__ __forceinline__ void bar_sync(int id, int n) { asm volatile("bar.sync %0, %1;" ::"r"(id), "r"(n) : "memory"); }
__device__ __forceinline__ void bar_arrive(int id, int n) { asm volatile("bar.arrive %0, %1;" ::"r"(id), "r"(n) : "memory"); }
template <int ID> __device__ __forceinline__ void bar_sync_wg(int wg) {
    if (BARP & 1) asm volatile("{.reg .pred p; setp.ne.u32 p, %0, 0; @p bar.sync %2, 256; @!p bar.sync %1, 256;}" ::"r"(wg), "n"(ID), "n"(ID + 1) : "memory");
    else bar_sync(ID + wg, 256);
}
template <int ID> __device__ __forceinline__ void bar_arrive_wg(int wg) {
    if (BARP & 2) asm volatile("{.reg .pred p; setp.ne.u32 p, %0, 0; @p bar.arrive %2, 256; @!p bar.arrive %1, 256;}" ::"r"(wg), "n"(ID), "n"(ID + 1) : "memory");
    else bar_arrive(ID + wg, 256);
}
__device__ __forceinline__ void mbar_init(uint32_t a, uint32_t cnt) { asm volatile("mbarrier.init.shared::cta.b64 [%0], %1;" ::"r"(a), "r"(cnt) : "memory"); }
__device__ __forceinline__ void mbar_expect_tx(uint32_t a, uint32_t bytes) { asm volatile("mbarrier.arrive.expect_tx.shared::cta.b64 _, [%0], %1;" ::"r"(a), "r"(bytes) : "memory"); }
__device__ __forceinline__ void mbar_wait(uint32_t a, uint32_t parity) {
    asm volatile("{.reg .pred p, q; .reg .u32 g; mov.u32 g, 0;\n"
                 "L: mbarrier.try_wait.parity.shared::cta.b64 p, [%0], %1;\n"
                 "add.u32 g, g, 1; setp.lt.and.u32 q, g, 0x400000, !p; @q bra L;}" ::"r"(a), "r"(parity) : "memory");
}
__device__ __forceinline__ bool mbar_test(uint32_t a, uint32_t parity) {
    uint32_t ok;
    asm volatile("{.reg .pred p; mbarrier.test_wait.parity.shared::cta.b64 p, [%1], %2; selp.u32 %0, 1, 0, p;}" : "=r"(ok) : "r"(a), "r"(parity) : "memory");
    return ok;
}
__device__ __forceinline__ bool elect() {
    uint32_t ok;
    asm volatile("{.reg .pred p; elect.sync _|p, 0xffffffff; selp.u32 %0, 1, 0, p;}" : "=r"(ok));
    return ok;
}
__device__ __forceinline__ void tma_box(const CUtensorMap* tm, uint32_t dst, uint32_t bar, int xq, int yq) {
    mbar_expect_tx(bar, XSTG / 4);
    asm volatile("cp.async.bulk.tensor.3d.shared::cluster.global.mbarrier::complete_tx::bytes [%0], [%1, {%3, %4, %5}], [%2];"
                 ::"r"(dst), "l"(tm), "r"(bar), "r"(0), "r"(xq), "r"(yq) : "memory");
}
__device__ __forceinline__ void tma_x(const CUtensorMap* tm, int slot, int q, int xq, int yq) { tma_box(tm, S_X + slot * XSTG + q * (XSTG / 4), S_BAR + 8 * slot, xq, yq); }
__device__ __forceinline__ void bulk_load(uint32_t dst, const void* src, uint32_t bytes, uint32_t bar) {
    mbar_expect_tx(bar, bytes);
    asm volatile("cp.async.bulk.shared::cluster.global.mbarrier::complete_tx::bytes [%0], [%1], %2, [%3];"
                 ::"r"(dst), "l"(src), "r"(bytes), "r"(bar) : "memory");
}
__device__ __forceinline__ void bulk_store(void* dst, uint32_t src, uint32_t bytes) {
    asm volatile("cp.async.bulk.global.shared::cta.bulk_group [%0], [%1], %2;" ::"l"(dst), "r"(src), "r"(bytes) : "memory");
}
__device__ __forceinline__ void bulk_commit() { asm volatile("cp.async.bulk.commit_group;" ::: "memory"); }
__device__ __forceinline__ void bulk_wait() { asm volatile("cp.async.bulk.wait_group 0;" ::: "memory"); }
__device__ __forceinline__ uint32_t lds32(uint32_t a) { uint32_t v; asm volatile("ld.shared.b32 %0, [%1];" : "=r"(v) : "r"(a)); return v; }
__device__ __forceinline__ void lds128(uint32_t* r, uint32_t a) { asm volatile("ld.shared.v4.b32 {%0,%1,%2,%3}, [%4];" : "=r"(r[0]), "=r"(r[1]), "=r"(r[2]), "=r"(r[3]) : "r"(a)); }
__device__ __forceinline__ void sts32(uint32_t a, uint32_t v) { asm volatile("st.shared.b32 [%0], %1;" ::"r"(a), "r"(v)); }
__device__ __forceinline__ void sts128(uint32_t a, uint32_t x, uint32_t y, uint32_t z, uint32_t w) { asm volatile("st.shared.v4.b32 [%0], {%1,%2,%3,%4};" ::"r"(a), "r"(x), "r"(y), "r"(z), "r"(w)); }
__device__ __forceinline__ void ldsm4(uint32_t& r0, uint32_t& r1, uint32_t& r2, uint32_t& r3, uint32_t a) {
    asm volatile("ldmatrix.sync.aligned.m8n8.x4.shared.b16 {%0,%1,%2,%3}, [%4];" : "=r"(r0), "=r"(r1), "=r"(r2), "=r"(r3) : "r"(a));
}
__device__ __forceinline__ void ldsm4(uint32_t* r, uint32_t a) { ldsm4(r[0], r[1], r[2], r[3], a); }
__device__ __forceinline__ void ldsm2(uint32_t& r0, uint32_t& r1, uint32_t a) {
    asm volatile("ldmatrix.sync.aligned.m8n8.x2.shared.b16 {%0,%1}, [%2];" : "=r"(r0), "=r"(r1) : "r"(a));
}
__device__ __forceinline__ void stsm4(uint32_t a, const uint32_t* r) {
    asm volatile("stmatrix.sync.aligned.m8n8.x4.shared.b16 [%4], {%0,%1,%2,%3};" ::"r"(r[0]), "r"(r[1]), "r"(r[2]), "r"(r[3]), "r"(a));
}
__device__ __forceinline__ uint32_t bfma(uint32_t a, uint32_t b, uint32_t c) { uint32_t d; asm("fma.rn.bf16x2 %0, %1, %2, %3;" : "=r"(d) : "r"(a), "r"(b), "r"(c)); return d; }
__device__ __forceinline__ uint32_t bmul(uint32_t a, uint32_t b) { uint32_t d; asm("mul.rn.bf16x2 %0, %1, %2;" : "=r"(d) : "r"(a), "r"(b)); return d; }
__device__ __forceinline__ uint32_t badd(uint32_t a, uint32_t b) { uint32_t d; asm("add.rn.bf16x2 %0, %1, %2;" : "=r"(d) : "r"(a), "r"(b)); return d; }
__device__ __forceinline__ uint32_t vfma(uint32_t a, uint32_t b, uint32_t c) { uint32_t d; asm volatile("fma.rn.bf16x2 %0, %1, %2, %3;" : "=r"(d) : "r"(a), "r"(b), "r"(c)); return d; }
__device__ __forceinline__ void vacc(uint32_t& d, uint32_t a, uint32_t b) { asm volatile("fma.rn.bf16x2 %0, %1, %2, %0;" : "+r"(d) : "r"(a), "r"(b)); }
__device__ __forceinline__ uint32_t vadd(uint32_t a, uint32_t b) { uint32_t d; asm volatile("add.rn.bf16x2 %0, %1, %2;" : "=r"(d) : "r"(a), "r"(b)); return d; }
__device__ __forceinline__ uint32_t vsub(uint32_t a, uint32_t b) { uint32_t d; asm volatile("sub.rn.bf16x2 %0, %1, %2;" : "=r"(d) : "r"(a), "r"(b)); return d; }
__device__ __forceinline__ uint32_t vmul(uint32_t a, uint32_t b) { uint32_t d; asm volatile("mul.rn.bf16x2 %0, %1, %2;" : "=r"(d) : "r"(a), "r"(b)); return d; }
__device__ __forceinline__ uint32_t habsmax(uint32_t a, uint32_t b) { uint32_t d; asm("max.xorsign.abs.bf16x2 %0, %1, %2;" : "=r"(d) : "r"(a), "r"(b)); return d; }
__device__ __forceinline__ float bf_lo(uint32_t v) { return __uint_as_float(v << 16); }
__device__ __forceinline__ float bf_hi(uint32_t v) { return __uint_as_float(v & 0xffff0000u); }
__device__ __forceinline__ uint32_t pack_h2(float lo, float hi) { uint32_t d; asm("cvt.rn.f16x2.f32 %0, %1, %2;" : "=r"(d) : "f"(hi), "f"(lo)); return d; }
__device__ __forceinline__ uint32_t pack_b2(float lo, float hi) { uint32_t d; asm("cvt.rn.bf16x2.f32 %0, %1, %2;" : "=r"(d) : "f"(hi), "f"(lo)); return d; }
__device__ __forceinline__ uint32_t b2h(uint32_t v) { return v + 7u * (v & 0x7fff7fffu); }
__device__ __forceinline__ float rsq(float v) { float r; asm("rsqrt.approx.ftz.f32 %0, %1;" : "=f"(r) : "f"(v)); return r; }

struct Conv {
    uint32_t w[50];
    uint32_t s[20];
    uint32_t accA[4][8], accB[4][4];
    uint32_t sink;
    bool on;
    uint32_t xa[2][12], xb[2][8];
};
template <int S, int P, int MODE>
__device__ __forceinline__ void tap_col(uint32_t x, const uint32_t* w, uint32_t (&d)[S], const uint32_t (&src)[S]) {
#pragma unroll
    for (int j = 4; j >= 0; j--) {
        const int q = P - j;
        if (q < 0 || q >= S) continue;
        if (j > 0 || MODE == 0) vacc(d[q], x, w[2 * j]);
        else if (MODE == 1) d[q] = vmul(x, w[0]);
        else d[q] = vfma(x, w[0], src[q]);
    }
}
template <int R, int K> __device__ __forceinline__ void conv_ld(Conv& c, uint32_t a1) {
    ldsm4(c.xa[R][2 * K + 2], c.xb[R][2 * K], c.xa[R][2 * K + 3], c.xb[R][2 * K + 1], a1 + K * 2 * PX);
}
#define CFN(n) { if ((CFENCE >> n) & 1) cfence(c.sink, c.on); }
#define ALLCOLS CA(0); CA(1); CA(2); CB(0); CA(3); CB(1); CA(4); CB(2); CA(5); CB(3); CA(6); CB(4); CA(7); CB(5); CA(8); CB(6); CA(9); CB(7); CA(10); CA(11);
template <int R, typename Fn>
__device__ __forceinline__ void conv_out(Conv& c, uint32_t sA, uint32_t sB, Fn before_store) {
#define CA(p) tap_col<8, p, 0>(c.xa[R][p], c.w + 41, c.accA[R], c.accA[R])
#define CB(p) tap_col<4, p, 0>(c.xb[R][p], c.w + 40, c.accB[R], c.accB[R])
    CA(0); CA(1); CA(2); CB(0); CA(3); CB(1); CA(4); CB(2); CA(5); CB(3); CA(6); CB(4); CA(7); CB(5);
    before_store();
    stsm4(sA, c.accA[R]);
    CA(8); CB(6); CA(9); CB(7); CA(10); CA(11);
    stsm4(sB, c.accB[R]);
    stsm4(sA + 4 * CPITCH, c.accA[R] + 4);
#undef CA
#undef CB
}
template <int S, int P, int R, bool OLD, bool NEW>
__device__ __forceinline__ void diff_col(const uint32_t (&x)[2][S + 4], const uint32_t* w, uint32_t (&acc)[4][S]) {
    if (!OLD && !NEW) return;
    const uint32_t d = vsub(x[0][P], x[1][P]);
    if (R == 1) {
        if (OLD) tap_col<S, P, 0>(d, w + 20, acc[0], acc[0]);
        if (NEW) tap_col<S, P, 2>(d, w, acc[2], acc[3]);
    } else {
        if (OLD) tap_col<S, P, 0>(d, w + 30, acc[1], acc[1]);
        if (NEW) tap_col<S, P, 0>(d, w + 10, acc[3], acc[3]);
    }
}
template <int R, bool OLD, bool NEW, typename Fn>
__device__ __forceinline__ void conv_rest(Conv& c, uint32_t a1, uint32_t a2, Fn mid) {
    if (R == 1) {
        if (OLD) {
#define CA(p) tap_col<8, p, 1>(c.xa[1][p], c.s + 11, c.accA[0], c.accA[0])
#define CB(p) tap_col<4, p, 1>(c.xb[1][p], c.s + 10, c.accB[0], c.accB[0])
            ALLCOLS
#undef CA
#undef CB
#pragma unroll
            for (int q = 0; q < 8; q++) { c.accA[1][q] = vadd(c.accA[3][q], c.accA[0][q]); c.accA[0][q] = vadd(c.accA[2][q], c.accA[0][q]); }
#pragma unroll
            for (int q = 0; q < 4; q++) { c.accB[1][q] = vadd(c.accB[3][q], c.accB[0][q]); c.accB[0][q] = vadd(c.accB[2][q], c.accB[0][q]); }
            CFN(7)
        }
        if (NEW) {
#define CA(p) tap_col<8, p, 1>(c.xa[1][p], c.s + 1, c.accA[3], c.accA[3])
#define CB(p) tap_col<4, p, 1>(c.xb[1][p], c.s, c.accB[3], c.accB[3])
            ALLCOLS
#undef CA
#undef CB
            CFN(8)
        }
    }
#define CA(p) diff_col<8, p, R, OLD, NEW>(c.xa, c.w + 1, c.accA)
#define CB(p) diff_col<4, p, R, OLD, NEW>(c.xb, c.w, c.accB)
    CA(0); CA(1); CFN(0)
    ldsm2(c.xa[1 - R][0], c.xa[1 - R][1], a2);
    CA(2); CB(0); CA(3); CB(1); CFN(1)
    conv_ld<1 - R, 0>(c, a1);
    CA(4); CB(2); CA(5); CB(3); CFN(2)
    conv_ld<1 - R, 1>(c, a1);
    CA(6); CB(4); CA(7); CB(5); CFN(3)
    conv_ld<1 - R, 2>(c, a1);
    CA(8); CB(6); CA(9); CB(7); CFN(4)
    conv_ld<1 - R, 3>(c, a1);
    CA(10); CA(11); CFN(5)
    ldsm2(c.xa[1 - R][10], c.xa[1 - R][11], a2 + 10 * PX);
    mid();
    CFN(9)
#undef CA
#undef CB
}
#undef ALLCOLS

template <int J, int K0, int K1> __device__ __forceinline__ void gemm1(uint32_t* H, const uint32_t* a1, uint64_t db) {
#pragma unroll
    for (int kk = K0; kk < K1; kk++) {
        const uint64_t d = mkd(db, D_W1 + ((2 * kk * 48 + J * 12) * 128 >> 4));
        if (kk == 0) wg_n96_h<0>(H + J * 24, a1, d);
        else wg_n96_h<1>(H + J * 24, a1 + 4 * kk, d);
    }
}
template <int K0, int K1> __device__ __forceinline__ void gemm2(uint32_t* acc, const uint32_t* H, uint64_t db) {
#pragma unroll
    for (int ks = K0; ks < K1; ks++) {
        const uint64_t d = mkd(db, D_W2 + (2 * ks * 12 * 128 >> 4));
        if (ks == 0) wg_n96_h<0>(acc, H, d);
        else wg_n96_h<1>(acc, H + 4 * ks, d);
    }
}
template <int N> __device__ __forceinline__ void gelu_a(uint32_t* t, const uint32_t* h) {
#pragma unroll
    for (int i = 0; i < N; i++) {
        uint32_t p, u;
        asm("fma.rn.f16x2 %0, %1, %1, %2;" : "=r"(p) : "r"(h[i]), "r"(GK2));
        asm("mul.rn.f16x2 %0, %1, %2;" : "=r"(u) : "r"(h[i]), "r"(p));
        if (i < N - NUP) {
            uint32_t a, b;
            asm("{.reg .b16 l, h, x; mov.b32 {l, h}, %2; tanh.approx.f16 x, l; cvt.u32.u16 %0, x; tanh.approx.f16 x, h; cvt.u32.u16 %1, x;}" : "=r"(a), "=r"(b) : "r"(u));
            asm volatile("prmt.b32 %0, %1, %2, 0x5410;" : "=r"(t[i]) : "r"(a), "r"(b));
        } else asm("tanh.approx.f16x2 %0, %1;" : "=r"(t[i]) : "r"(u));
    }
    pin<N>(t);
}
template <int N> __device__ __forceinline__ void gelu_b(uint32_t* h, const uint32_t* t) {
#pragma unroll
    for (int i = 0; i < N; i++) asm volatile("fma.rn.f16x2 %0, %1, %2, %1;" : "=r"(h[i]) : "r"(h[i]), "r"(t[i]));
}
template <int r> __device__ __forceinline__ void ln_part(const uint32_t* a, uint32_t* sq) {
    uint32_t s[6], q[2];
#pragma unroll
    for (int i = 0; i < 6; i++) s[i] = badd(a[4 * i + r], a[4 * i + 2 + r]);
    sq[r] = badd(badd(badd(s[0], s[1]), badd(s[2], s[3])), badd(s[4], s[5]));
#pragma unroll
    for (int i = 0; i < 12; i++) q[i & 1] = (i < 2) ? bmul(a[2 * i + r], a[2 * i + r]) : bfma(a[2 * i + r], a[2 * i + r], q[i & 1]);
    sq[2 + r] = badd(q[0], q[1]);
    pin<1>(sq + r); pin<1>(sq + 2 + r);
}
__device__ __forceinline__ void ln_mma(float* d, const uint32_t* sq, uint64_t db) {
    asm volatile("wgmma.mma_async.sync.aligned.m64n8k16.f32.bf16.bf16 {%0,%1,%2,%3}, {%4,%5,%6,%7}, %8, 0, 1, 1, 1;"
                 : "=f"(d[0]), "=f"(d[1]), "=f"(d[2]), "=f"(d[3]) : "r"(sq[0]), "r"(sq[1]), "r"(sq[2]), "r"(sq[3]), "l"(mkd(db, D_ST)));
}
__device__ __forceinline__ bool ln_fin(float* d, uint32_t* st) {
    pin<4>(d);
    bool risky = false;
#pragma unroll
    for (int r = 0; r < 2; r++) {
        const float q = rsq(fmaf(-d[2 * r], d[2 * r], d[2 * r + 1] + LN_EPS * (CH * CH)));
        const float z = d[2 * r] * q;
        risky |= !(fabsf(z) <= 1.f);
        st[r] = pack_b2(q * (LN_OUT * CH), z * -LN_OUT);
    }
    pin<2>(st);
    return __any_sync(0xffffffffu, risky);
}
__device__ __forceinline__ void ln_fix(uint32_t* a, const float* d, uint32_t* st) {
#pragma unroll
    for (int r = 0; r < 2; r++) {
        const uint32_t m2 = pack_b2(d[2 * r] * (-1.f / CH), d[2 * r] * (-1.f / CH));
        uint32_t q[2];
#pragma unroll
        for (int i = 0; i < 12; i++) {
            a[2 * i + r] = badd(a[2 * i + r], m2);
            q[i & 1] = (i < 2) ? bmul(a[2 * i + r], a[2 * i + r]) : bfma(a[2 * i + r], a[2 * i + r], q[i & 1]);
        }
        const uint32_t qq = badd(q[0], q[1]);
        float v = bf_lo(qq) + bf_hi(qq);
        v += __shfl_xor_sync(0xffffffffu, v, 1);
        v += __shfl_xor_sync(0xffffffffu, v, 2);
        st[r] = pack_b2(rsq(fmaf(v, 1.f / CH, LN_EPS)) * LN_OUT, 0.f);
    }
}
template <int I0, int I1> __device__ __forceinline__ void ln_out(uint32_t* a, const uint32_t* b, const uint32_t* st) {
#pragma unroll
    for (int i = I0; i < I1; i++) {
        uint32_t v;
        asm("{.reg .b16 l, h; .reg .b32 ll, hh; mov.b32 {l, h}, %2; mov.b32 ll, {l, l}; mov.b32 hh, {h, h}; fma.rn.bf16x2 %0, %1, ll, hh;}"
            : "=r"(v) : "r"(b[i]), "r"(st[i & 1]));
        a[i] = b2h(v);
        pin<1>(a + i);
    }
}
template <int J0, int J1> __device__ __forceinline__ void epi_mma(float* d, const uint32_t* acc, uint64_t db) {
    const uint64_t ds = mkd(db, D_ID);
#pragma unroll
    for (int j = J0; j < J1; j++)
        asm volatile("wgmma.mma_async.sync.aligned.m64n16k16.f32.f16.f16 {%0,%1,%2,%3,%4,%5,%6,%7}, {%8,%9,%10,%11}, %12, 0, 1, 1, 1;"
                     : "=f"(d[8 * j]), "=f"(d[8 * j + 1]), "=f"(d[8 * j + 2]), "=f"(d[8 * j + 3]), "=f"(d[8 * j + 4]), "=f"(d[8 * j + 5]), "=f"(d[8 * j + 6]), "=f"(d[8 * j + 7])
                     : "r"(acc[4 * j]), "r"(acc[4 * j + 1]), "r"(acc[4 * j + 2]), "r"(acc[4 * j + 3]), "l"(ds));
}
template <int I> __device__ __forceinline__ void epi_red(const float* d, uint8_t* gp) {
#pragma unroll
    for (int r = 0; r < 2; r++) {
        uint32_t o[4];
#pragma unroll
        for (int jj = 0; jj < 4; jj++) o[jj] = pack_b2(d[16 * I + 4 * jj + 2 * r], d[16 * I + 4 * jj + 2 * r + 1]);
        asm volatile("red.global.add.noftz.v4.bf16x2 [%0], {%1,%2,%3,%4};" ::"l"(gp + r * 8 * PX + I * 64), "r"(o[0]), "r"(o[1]), "r"(o[2]), "r"(o[3]));
    }
}

struct Mlp {
    uint32_t H[96], a1[24], b[24], acc[24], st[2], sq[4], t[8], sink;
    float sd[4], dd[48];
    bool on;
};
template <bool FIRST, bool LAST>
__device__ __forceinline__ void mlp_tile(Mlp& m, const uint64_t db, const int wg, const uint32_t cb, uint8_t* op) {
    bool risky;
#define F wg_fence()
#define C wg_commit()
#define W(n) wg_wait<n>()
#define S cfence(m.sink, m.on);
#define FULL() { if (!LAST) bar_sync_wg<BAR_FULL>(wg); }
#define RELEASE() { if (!LAST) bar_arrive_wg<BAR_EMPTY>(wg); }
#define LDB(k0, k1) if (!LAST) { _Pragma("unroll") for (int kk = k0; kk < k1; kk++) ldsm4(m.b + 4 * kk, cb + kk * 32); }
#define GA8(p) { if (!LAST) gelu_a<8>(m.t, m.H + 8 * (p)); }
#define GAF(p) gelu_a<8>(m.t, m.H + 8 * (p))
#define GB8(p) gelu_b<8>(m.H + 8 * (p), m.t)
#define G1(j, k0, k1) { if (!LAST || j != 0) gemm1<j, k0, k1>(m.H, m.a1, db); }
#define G1C(j, k0, k1) { if (!LAST || j != 0) { gemm1<j, k0, k1>(m.H, m.a1, db); C; } }
#define G2(k0, k1) gemm2<k0, k1>(m.acc, m.H, db)
#define RDY(j) { if (!LAST || j != 0) pin<24>(m.H + (j) * 24); }
#define IDM(j0, j1) { if (!FIRST) epi_mma<j0, j1>(m.dd, m.acc, db); }
#define IDMC(j0, j1) { if (!FIRST) { epi_mma<j0, j1>(m.dd, m.acc, db); C; } }
#define IDR(j0, j1) { if (!FIRST) pin<8 * (j1 - j0)>(m.dd + 8 * j0); }
#define ER(k) { if (!FIRST) epi_red<k>(m.dd, op); }
#define LP(r) { if (!LAST) ln_part<r>(m.b, m.sq); }
#define LMC() { if (!LAST) { ln_mma(m.sd, m.sq, db); C; } }
#define LF() { if (!LAST) risky = ln_fin(m.sd, m.st); }
#define LX2() { if (!LAST && __builtin_expect(risky, 0)) ln_fix(m.b, m.sd, m.st); }
#define LO(i0, i1) { if (!LAST) ln_out<i0, i1>(m.a1, m.b, m.st); }
    F; IDMC(0,2); G1(1,0,1); G1(1,1,2); G1(1,2,3); G1(1,3,4); C; GB8(0); GAF(1); S
    W(1); IDR(0,2); ER(0); S F; IDM(2,6); G1(1,4,5); G1(1,5,6); C; GB8(1); GAF(2); S
    W(0); RDY(1); IDR(2,6); F; G2(0,1); G2(1,2); G2(2,3); G2(3,4); C; GB8(2); GAF(3); ER(1); S
    W(1); F; G2(4,5); G1(2,0,1); G2(5,6); G1(2,1,2); G1(2,2,3); G1(2,3,4); C; ER(2); GB8(3); GAF(4); S
    FULL() LDB(0,3)
    W(1); F; G1C(2,4,6); G2(6,7); G2(7,8); C; GB8(4); GAF(5);
    LDB(3,6)
    W(1); RDY(2); F; G2(8,9); G2(9,10); C; LP(0); LP(1); GB8(5); GAF(6); S
    W(1); F; LMC(); G2(10,11); G1(3,0,1); G2(11,12); G1(3,1,2); G1(3,2,3); G1(3,3,4); C; GB8(6); GAF(7);  S
    W(1); F; G1C(3,4,6); G2(12,13); G2(13,14); C; GB8(7); GAF(8); LF(); S
    LX2()
    W(1); RDY(3); F; G2(14,15); G2(15,16); C; LO(0,16); GB8(8); GAF(9); S
    W(1); F; G2(16,17); G1(0,0,1); G2(17,18); G1(0,1,2); G1(0,2,3); G1(0,3,4); C; LO(16,24); GB8(9); GAF(10); S
    W(1); F; G1C(0,4,6); G2(18,19); G2(19,20); C; GB8(10); GAF(11); S
    RELEASE()
    W(1); RDY(0); GB8(11); F; G2(20,21); G2(21,22); G2(22,23); G2(23,24); C; S GA8(0); S
    W(0);
    pin<24>(m.acc);
#undef F
#undef C
#undef W
#undef S
#undef FULL
#undef RELEASE
#undef LDB
#undef GA8
#undef GAF
#undef GB8
#undef G1
#undef G1C
#undef G2
#undef RDY
#undef IDM
#undef IDMC
#undef IDR
#undef ER
#undef LP
#undef LMC
#undef LF
#undef LX2
#undef LO
}

__global__ void __launch_bounds__(384, 1)
replk_kernel(const __grid_constant__ CUtensorMap tmx, const uint8_t* __restrict__ dwl, const uint8_t* __restrict__ dws,
             const uint8_t* __restrict__ w1, const uint8_t* __restrict__ w2, uint8_t* __restrict__ out, const uint64_t db,
             unsigned long long* __restrict__ dbg) {
    extern __shared__ __align__(1024) uint8_t smem[];
    const int tid = (threadIdx.x + ROT * 128) % 384, lane = tid & 31;
    const int warp = __shfl_sync(0xffffffffu, tid >> 5, 0);
    const int w0 = (blockIdx.x % (IMG_W / SW)) * SW, y0 = (blockIdx.x / (IMG_W / SW)) * RB;
    const int up = 1 & ~(blockIdx.x / (IMG_W / SW));
    const int dy = 1 - 2 * up, yb = y0 - 2 + (RB + 3) * up;
    if (tid == 0) sts32(S_RED + 40, (uint32_t)clock64());

    if (warp >= 8) {
        const int cw = warp - 8;
        const int tj = min((tid - 256) / 24, 4), tc = (tid - 256) % 24;
        uint2 ts[5], tl[3];
#pragma unroll
        for (int i = 0; i < 5; i++) ts[i] = __ldg(reinterpret_cast<const uint2*>(dws) + ((2 + dy * (i - 2)) * 5 + tj) * 24 + tc);
#pragma unroll
        for (int i = 0; i < 3; i++) tl[i] = __ldg(reinterpret_cast<const uint2*>(dwl) + ((1 + dy * (i - 1)) * 3 + (tj + 2) % 3) * 24 + tc);
        if (cw == 0 && elect()) {
            if ((uint32_t)__cvta_generic_to_shared(smem) != SB) __trap();
#pragma unroll
            for (int s = 0; s < NS; s++) mbar_init(S_BAR + 8 * s, 4);
            asm volatile("fence.mbarrier_init.release.cluster;" ::: "memory");
#pragma unroll
            for (int q = 0; q < 4; q++) tma_x(&tmx, 0, q, w0 - 2 + (q & 1) * 18, yb + dy * (q >> 1));
        }
        bar_sync(BAR_CV, 128);
        const int xq = w0 - 2 + (cw & 1) * 18, yq = yb + dy * (cw >> 1);
        if (elect()) tma_x(&tmx, 1, cw, xq, yq + 2 * dy);
        Conv c;
        {
            const uint32_t lm = (tj & 3) ? ~0u : 0u;
            uint32_t v[7][2];
#pragma unroll
            for (int i = 0; i < 5; i++) {
                v[i][0] = ts[i].x; v[i][1] = ts[i].y;
                if (i >= 1 && i <= 3) { v[i][0] = badd(v[i][0], tl[i - 1].x & lm); v[i][1] = badd(v[i][1], tl[i - 1].y & lm); }
                v[i][0] = bmul(v[i][0], WSC2); v[i][1] = bmul(v[i][1], WSC2);
            }
#pragma unroll
            for (int u = 0; u < 2; u++) { v[5][u] = badd(v[0][u], v[1][u]); v[6][u] = badd(v[2][u], v[3][u]); }
#pragma unroll
            for (int i = 0; i < 7; i++)
                asm volatile("st.shared.v2.b32 [%0], {%1, %2};" ::"r"(S_C + ((i * 5 + tj) * 24 + tc) * 8), "r"(v[i][0]), "r"(v[i][1]) : "memory");
            bar_sync(BAR_CV, 128);
            if (elect()) tma_x(&tmx, 2, cw, xq, yq + 4 * dy);
            const int qd = lane & 7, u = (lane >> 3) & 1;
            const uint32_t ws = S_C + ((cw < 2 + u) ? qd : 8 + (qd & 3)) * 16;
#pragma unroll
            for (int k = 0; k < 12; k++) ldsm4(c.w + 4 * k, ws + ((lane >> 4) + 2 * k) * PX);
            ldsm2(c.w[48], c.w[49], ws + 24 * PX);
#pragma unroll
            for (int k = 0; k < 5; k++) ldsm4(c.s + 4 * k, ws + ((lane >> 4) + 25 + 2 * k) * PX);
        }
        const int mi = lane >> 3, qd = lane & 7;
        const int chA = (cw < 3) ? qd : 8 + (qd & 3), pxA = (cw < 3) ? 8 * cw : 16 * (qd >> 2);
        const int chB = (cw < 2) ? qd : 8 + (qd & 3), pxB = (cw < 2) ? 24 + 4 * cw : 16 * (qd >> 2) + 8 + 4 * (cw - 2);
        const uint32_t a1 = S_X + ((mi & 1) ? (pxB + (mi >> 1)) * PX + chB * 16 : (pxA + 2 + (mi >> 1)) * PX + chA * 16);
        const uint32_t a2 = S_X + (pxA + (mi & 1)) * PX + chA * 16;
        uint32_t qA = S_C + (pxA >> 4) * CGRP + ((pxA & 15) + mi) * CPITCH + chA * 16;
        uint32_t qB = S_C + (pxB >> 4) * CGRP + ((pxB & 15) + mi) * CPITCH + chB * 16;
        auto nop = [] {};
        c.sink = lane; c.on = lane == (int)(db >> 8);
        mbar_wait(S_BAR, 0);
        ldsm2(c.xa[0][0], c.xa[0][1], a2);
        conv_ld<0, 0>(c, a1); conv_ld<0, 1>(c, a1); conv_ld<0, 2>(c, a1); conv_ld<0, 3>(c, a1);
        ldsm2(c.xa[0][10], c.xa[0][11], a2 + 10 * PX);
        conv_rest<0, false, false>(c, a1 + XROW, a2 + XROW, nop);
        if (elect()) tma_x(&tmx, 3, cw, xq, yq + 6 * dy);
        mbar_wait(S_BAR + 8, 0);
        const uint32_t xs0 = S_X + (cw >> 1) * XROW + (2 + 16 * (cw & 1)) * PX;
        uint8_t* op = out + (size_t)((yq + 2 * dy) * IMG_W + w0 + 16 * (cw & 1)) * PX;
        const int64_t ostep = 2 * dy * IMG_W * PX;
        if (elect()) bulk_store(op, xs0 + XSTG, 16 * PX);
        bulk_commit();
        conv_rest<1, false, true>(c, a1 + XSTG, a2 + XSTG, nop);
        conv_rest<0, false, true>(c, a1 + XSTG + XROW, a2 + XSTG + XROW, nop);
        bar_sync(BAR_CV, 128);
        if (elect()) tma_x(&tmx, 0, cw, xq, yq + 8 * dy);
        mbar_wait(S_BAR + 16, 0);
        uint32_t u;
        asm volatile("mov.u32 %0, 24;" : "=r"(u));
        const uint32_t xd0 = S_X + cw * (XSTG / 4) - S_BAR * (XSTG / 8);
        uint32_t xo = 2 * XSTG, bid = BAR_EMPTY;
        int dq = CBUF, yn = yq + 10 * dy;
#pragma unroll 1
        for (;;) {
            const uint32_t nb = S_BAR | (u & 24), np = u >> 5;
            bool ok;
            conv_rest<1, true, true>(c, a1 + xo, a2 + xo, nop);
            conv_out<0>(c, qA, qB, [&] {
                bulk_wait();
                op += ostep;
                bar_sync(bid, 256);
                if (elect()) {
                    tma_box(&tmx, (nb ^ 16) * (XSTG / 8) + xd0, nb ^ 16, xq, u < 8 * NT ? yn : -8);
                    bulk_store(op, xs0 + xo, 16 * PX);
                }
                bulk_commit();
            });
            CFN(6)
            conv_rest<0, true, true>(c, a1 + xo + XROW, a2 + xo + XROW, [&] { ok = mbar_test(nb, np); });
            conv_out<1>(c, qA + 2 * CGRP, qB + 2 * CGRP, nop);
            bar_arrive(bid - (BAR_EMPTY - BAR_FULL), 256);
            xo = (u & 24) * (XSTG / 8); qA += dq; qB += dq; dq = -dq;
            asm volatile("" : "+r"(xo));
            yn += 2 * dy; bid ^= 1; u += 8;
            if (ok && u < 8 * (NT + 2)) continue;
            mbar_wait(nb, np);
            if (u == 8 * (NT + 2)) break;
        }
        conv_rest<1, true, false>(c, a1 + xo, a2 + xo, nop);
        conv_out<0>(c, qA, qB, [&] { bulk_wait(); bar_sync(BAR_EMPTY + 1, 256); });
        conv_rest<0, true, false>(c, a1 + xo + XROW, a2 + xo + XROW, nop);
        conv_out<1>(c, qA + 2 * CGRP, qB + 2 * CGRP, nop);
        bar_arrive(BAR_FULL + 1, 256);
        bar_arrive(BAR_EMPTY, 256);
        bar_arrive(BAR_EMPTY + 1, 256);
        mbar_wait(S_BAR + 8 * 2, 0);
        mbar_wait(S_BAR + 8 * 3, 0);
        if (dbg) sts32(S_RED + 36, c.sink);
    } else {
        const int wg = warp >> 2, wq = warp & 3;
        if (warp == 0 && elect()) {
#pragma unroll
            for (int s = 0; s < 5; s++) mbar_init(S_WBAR + 8 * s, 1);
            asm volatile("fence.mbarrier_init.release.cluster;" ::: "memory");
#pragma unroll
            for (int i = 0; i < 2; i++) bulk_load(S_W2 + i * (WBYTES / 2), w2 + i * (WBYTES / 2), WBYTES / 2, S_WBAR + 24 + 8 * i);
        }
        bar_arrive(BAR_EMPTY + wg, 256);
        if (tid < 64) sts32(S_ST + tid * 4, tid < 32 ? 0x00003f80u : 0x42c00000u);
        bar_sync(BAR_W, 256);
        {
            uint32_t r[18][4], mx = 0;
#pragma unroll
            for (int h = 0; h < 2; h++) {
                mbar_wait(S_WBAR + 24 + 8 * h, 0);
                if (h == 0 && warp == 0 && elect()) {
#pragma unroll
                    for (int i = 0; i < 3; i++) bulk_load(S_W1 + i * (WBYTES / 3), w1 + i * (WBYTES / 3), WBYTES / 3, S_WBAR + 8 * i);
                }
#pragma unroll
                for (int j = 0; j < 9; j++) {
                    uint32_t* q = r[h * 9 + j];
                    lds128(q, S_W2 + h * (WBYTES / 2) + (warp * 3 + j / 3) * 1536 + (lane >> 2) * PX + (j % 3) * 64 + (lane & 3) * 16);
                    mx = habsmax(habsmax(mx, q[0]), habsmax(habsmax(q[1], q[2]), q[3]));
                }
            }
            mx &= 0x7fff7fffu;
            mx = __reduce_max_sync(0xffffffffu, max(mx >> 16, mx & 0xffffu));
            if (lane == 0) sts32(S_RED + warp * 4, mx);
            bar_sync(BAR_W, 256);
            mx = __reduce_max_sync(0xffffffffu, lds32(S_RED + (lane & 7) * 4));
            const int e = max(min(123 - (int)(mx >> 7), 14), -14);
            const uint32_t wsc2 = (uint32_t)(15 + e) * 0x00800080u;
            if (tid < 128) {
                const int cm = tid >> 5, k = (tid >> 2) & 7, q = tid & 3;
                const uint32_t cv = INV2A_H - (e << 10);
                sts32(S_ID + tid * 4, (cm == 0 || cm == 3) && (k >> 1) == q ? cv << (16 * (k & 1)) : 0u);
            }
#pragma unroll
            for (int j = 0; j < 18; j++) {
#pragma unroll
                for (int k = 0; k < 4; k++) r[j][k] = b2h(bmul(r[j][k], wsc2));
                stsm4(S_W2 + (j / 9) * (WBYTES / 2) + (warp * 3 + j % 9 / 3) * 1536 + (j % 3) * 512 + lane * 16, r[j]);
            }
        }
        {
            const int kr = lane & 7, nb = (kr + wg * 4 + (lane >> 3)) & 7;
#pragma unroll 1
            for (int i = 0; i < 3; i++) {
                const uint32_t base = S_W1 + (i * 4 + wq) * 6144;
                uint32_t r[6][4];
                mbar_wait(S_WBAR + 8 * i, 0);
#pragma unroll
                for (int j = 0; j < 6; j++) lds128(r[j], base + kr * 768 + (j * 8 + nb) * 16);
                bar_sync(BAR_PAIR + wq, 64);
#pragma unroll
                for (int j = 0; j < 6; j++)
                    sts128(base + kr * 16 + (j * 8 + nb) * 128, pack_h2(bf_lo(r[j][0]), bf_hi(r[j][0])), pack_h2(bf_lo(r[j][1]), bf_hi(r[j][1])),
                           pack_h2(bf_lo(r[j][2]), bf_hi(r[j][2])), pack_h2(bf_lo(r[j][3]), bf_hi(r[j][3])));
            }
        }
        asm volatile("fence.proxy.async.shared::cta;" ::: "memory");
        const uint32_t cb = S_C + wg * CBUF + wq * CGRP + (lane & 15) * CPITCH + (lane >> 4) * 16;
        const uint32_t goff = ((yb + dy * (2 + 2 * wg + (wq >> 1))) * IMG_W + w0 + (wq & 1) * 16 + (lane >> 2)) * PX + (lane & 3) * 16;
        const int64_t gstep = dy * TSTEP;
        uint8_t* op = out;
        Mlp m;
        m.sink = lane; m.on = lane == (int)(db >> 8);
        bar_sync(BAR_W, 256);
        bar_sync(BAR_FULL + wg, 256);
#pragma unroll
        for (int kk = 0; kk < 6; kk++) ldsm4(m.b + 4 * kk, cb + kk * 32);
        bar_arrive(BAR_EMPTY + wg, 256);
        ln_part<0>(m.b, m.sq); ln_part<1>(m.b, m.sq);
        wg_fence(); ln_mma(m.sd, m.sq, DB); wg_commit(); wg_wait<0>();
        if (ln_fin(m.sd, m.st)) ln_fix(m.b, m.sd, m.st);
        ln_out<0, 24>(m.a1, m.b, m.st);
        wg_fence(); gemm1<0, 0, 6>(m.H, m.a1, DB); wg_commit(); wg_wait<0>();
        pin<24>(m.H);
        gelu_a<8>(m.t, m.H);
        mlp_tile<true, false>(m, DB, wg, cb, nullptr);
        int i;
        asm volatile("mov.u32 %0, 1;" : "=r"(i));
#pragma unroll 1
        do {
            mlp_tile<false, false>(m, db, wg, cb, op + goff);
            op += gstep;
            asm volatile("" : "+l"(op));
        } while (++i < NT / 2 - 1);
        op += goff;
        mlp_tile<false, true>(m, db, wg, cb, op);
        op += gstep;
        wg_fence(); epi_mma<0, 6>(m.dd, m.acc, db); wg_commit(); wg_wait<0>();
        pin<48>(m.dd);
        epi_red<0>(m.dd, op); epi_red<1>(m.dd, op); epi_red<2>(m.dd, op);
        if (dbg) {
            sts32(S_RED + 36, m.sink);
            uint32_t tx;
            asm volatile("mov.u32 %0, %%tid.x;" : "=r"(tx));
            if ((tx & 127) == 0) atomicAdd(dbg + (tx >> 7), (unsigned long long)((uint32_t)clock64() - lds32(S_RED + 40)));
        }
    }
}
#undef CFN

typedef CUresult (*EncodeFn)(CUtensorMap*, CUtensorMapDataType, cuuint32_t, void*, const cuuint64_t*, const cuuint64_t*,
                             const cuuint32_t*, const cuuint32_t*, CUtensorMapInterleave, CUtensorMapSwizzle,
                             CUtensorMapL2promotion, CUtensorMapFloatOOBfill);

}

#define DBG_PTR nullptr
extern "C" void kernel_launch(void* const* d_in, const int* in_sizes, int n_in, void* d_out, int out_size) {
    static EncodeFn enc = nullptr;
    if (!enc) {
        void* fn = nullptr;
        cudaDriverEntryPointQueryResult qr;
        cudaGetDriverEntryPoint("cuTensorMapEncodeTiled", &fn, cudaEnableDefault, &qr);
        enc = (EncodeFn)fn;
        cudaFuncSetAttribute(replk_kernel, cudaFuncAttributeMaxDynamicSharedMemorySize, SMEM_BYTES);
    }
    CUtensorMap tm;
    const cuuint64_t gdim[3] = {CH, IMG_W, IMG_H};
    const cuuint64_t gstr[2] = {PX, (cuuint64_t)IMG_W * PX};
    const cuuint32_t box[3] = {CH, (SW + 4) / 2, 1};
    const cuuint32_t estr[3] = {1, 1, 1};
    enc(&tm, CU_TENSOR_MAP_DATA_TYPE_BFLOAT16, 3, d_in[0], gdim, gstr, box, estr, CU_TENSOR_MAP_INTERLEAVE_NONE,
        CU_TENSOR_MAP_SWIZZLE_NONE, CU_TENSOR_MAP_L2_PROMOTION_L2_128B, CU_TENSOR_MAP_FLOAT_OOB_FILL_NONE);
    replk_kernel<<<(IMG_W / SW) * (IMG_H / RB), 384, SMEM_BYTES>>>(
        tm, (const uint8_t*)d_in[1], (const uint8_t*)d_in[2], (const uint8_t*)d_in[3], (const uint8_t*)d_in[4], (uint8_t*)d_out, DB, DBG_PTR);
}
```

```cpp
#include <cuda_runtime.h>
#include <cuda.h>
#include <stdint.h>

namespace {

#define CFENCE 0x314
#define HOLD 4
#define YLAG 2
#define BARP 3
#define ROT 2

constexpr int IMG_H = 512, IMG_W = 512, CH = 96, HID = 384;
constexpr int SW = 32;
constexpr int RB = 64;
constexpr int NT = RB / 2;
constexpr int NS = 4;
constexpr int PX = CH * 2;
constexpr int XROW = (SW + 4) * PX;
constexpr int XSTG = 2 * XROW;
constexpr int CPITCH = 208;
constexpr int CGRP = 16 * CPITCH + 64;
constexpr int CBUF = 4 * CGRP;
constexpr int WBYTES = CH * HID * 2;
constexpr int TSTEP = 4 * IMG_W * PX;

constexpr uint32_t SB = 1024;
constexpr uint32_t S_W1 = SB;
constexpr uint32_t S_W2 = S_W1 + WBYTES;
constexpr uint32_t S_X = S_W2 + WBYTES;
constexpr uint32_t S_C = S_X + NS * XSTG;
constexpr uint32_t S_BAR = S_C + 2 * CBUF;
constexpr uint32_t S_WBAR = S_BAR + 8 * NS;
constexpr uint32_t S_RED = S_WBAR + 8 * 6;
constexpr uint32_t S_ST = S_BAR + 256;
constexpr uint32_t S_ID = S_ST + 384;
constexpr int SMEM_BYTES = S_ID + 512 - SB;
static_assert(SMEM_BYTES <= 232448 && S_BAR % 128 == 0, "smem");

constexpr int BAR_FULL = 1, BAR_EMPTY = 4, BAR_W = 6, BAR_CV = 8, BAR_PAIR = 9;

constexpr float GA = 0.3292034911525734f;
constexpr uint32_t GK2 = 0x40d940d9u;
constexpr uint32_t INV2A_H = 0x3e13u;
constexpr uint32_t WSC2 = (uint32_t)(127 - 48) * 0x00800080u;
constexpr float LN_EPS = 1e-5f * 0x1p-96f;
constexpr float LN_OUT = GA * 0x1p-112f;

constexpr uint64_t DB = (uint64_t)(128 >> 4) << 32;
constexpr uint32_t D_W1 = (S_W1 >> 4) | ((48 * 128 >> 4) << 16);
constexpr uint32_t D_W2 = (S_W2 >> 4) | ((12 * 128 >> 4) << 16);
constexpr uint32_t D_ST = (S_ST >> 4) | ((128 >> 4) << 16);
constexpr uint32_t D_ID = (S_ID >> 4) | ((256 >> 4) << 16);

template <int SCALE_D> __device__ __forceinline__ void wg_n96_h(uint32_t* d, const uint32_t* a, uint64_t desc);
template <>
__device__ __forceinline__ void wg_n96_h<0>(uint32_t* d, const uint32_t* a, uint64_t desc) {
    asm volatile("wgmma.mma_async.sync.aligned.m64n96k16.f16.f16.f16 {"
        "%0,%1,%2,%3,%4,%5,%6,%7,%8,%9,%10,%11,%12,%13,%14,%15,"
        "%16,%17,%18,%19,%20,%21,%22,%23},"
        "{%24,%25,%26,%27}, %28, 0, 1, 1, 1;"
        : "=r"(d[0]), "=r"(d[1]), "=r"(d[2]), "=r"(d[3]), "=r"(d[4]), "=r"(d[5]), "=r"(d[6]), "=r"(d[7]),
          "=r"(d[8]), "=r"(d[9]), "=r"(d[10]), "=r"(d[11]), "=r"(d[12]), "=r"(d[13]), "=r"(d[14]), "=r"(d[15]),
          "=r"(d[16]), "=r"(d[17]), "=r"(d[18]), "=r"(d[19]), "=r"(d[20]), "=r"(d[21]), "=r"(d[22]), "=r"(d[23])
        : "r"(a[0]), "r"(a[1]), "r"(a[2]), "r"(a[3]), "l"(desc));
}
template <>
__device__ __forceinline__ void wg_n96_h<1>(uint32_t* d, const uint32_t* a, uint64_t desc) {
    asm volatile("wgmma.mma_async.sync.aligned.m64n96k16.f16.f16.f16 {"
        "%0,%1,%2,%3,%4,%5,%6,%7,%8,%9,%10,%11,%12,%13,%14,%15,"
        "%16,%17,%18,%19,%20,%21,%22,%23},"
        "{%24,%25,%26,%27}, %28, 1, 1, 1, 1;"
        : "+r"(d[0]), "+r"(d[1]), "+r"(d[2]), "+r"(d[3]), "+r"(d[4]), "+r"(d[5]), "+r"(d[6]), "+r"(d[7]),
          "+r"(d[8]), "+r"(d[9]), "+r"(d[10]), "+r"(d[11]), "+r"(d[12]), "+r"(d[13]), "+r"(d[14]), "+r"(d[15]),
          "+r"(d[16]), "+r"(d[17]), "+r"(d[18]), "+r"(d[19]), "+r"(d[20]), "+r"(d[21]), "+r"(d[22]), "+r"(d[23])
        : "r"(a[0]), "r"(a[1]), "r"(a[2]), "r"(a[3]), "l"(desc));
}

__device__ __forceinline__ void wg_fence() { asm volatile("wgmma.fence.sync.aligned;" ::: "memory"); }
__device__ __forceinline__ void wg_commit() { asm volatile("wgmma.commit_group.sync.aligned;" ::: "memory"); }
template <int N> __device__ __forceinline__ void wg_wait() { asm volatile("wgmma.wait_group.sync.aligned %0;" ::"n"(N) : "memory"); }
template <int N> __device__ __forceinline__ void pin(uint32_t* r) {
#pragma unroll
    for (int i = 0; i < N; i++) asm volatile("" : "+r"(r[i])::"memory");
}
template <int N> __device__ __forceinline__ void pin(float* r) {
#pragma unroll
    for (int i = 0; i < N; i++) asm volatile("" : "+f"(r[i])::"memory");
}
__device__ __forceinline__ void cfence(uint32_t& sink, bool on) {
    asm volatile("{.reg .pred p; setp.ne.u32 p, %1, 0; @p mov.u32 %0, %%clock;}" : "+r"(sink) : "r"((uint32_t)on) : "memory");
}
__device__ __forceinline__ uint64_t mkd(uint64_t db, uint32_t lo) { uint64_t d; asm volatile("add.u64 %0, %1, %2;" : "=l"(d) : "l"(db), "l"((uint64_t)lo)); return d; }

__device__ __forceinline__ void bar_sync(int id, int n) { asm volatile("bar.sync %0, %1;" ::"r"(id), "r"(n) : "memory"); }
__device__ __forceinline__ void bar_arrive(int id, int n) { asm volatile("bar.arrive %0, %1;" ::"r"(id), "r"(n) : "memory"); }
template <int ID> __device__ __forceinline__ void bar_sync_wg(int wg) {
    if (BARP & 1) asm volatile("{.reg .pred p; setp.ne.u32 p, %0, 0; @p bar.sync %2, 256; @!p bar.sync %1, 256;}" ::"r"(wg), "n"(ID), "n"(ID + 1) : "memory");
    else bar_sync(ID + wg, 256);
}
template <int ID> __device__ __forceinline__ void bar_arrive_wg(int wg) {
    if (BARP & 2) asm volatile("{.reg .pred p; setp.ne.u32 p, %0, 0; @p bar.arrive %2, 256; @!p bar.arrive %1, 256;}" ::"r"(wg), "n"(ID), "n"(ID + 1) : "memory");
    else bar_arrive(ID + wg, 256);
}
__device__ __forceinline__ void mbar_init(uint32_t a, uint32_t cnt) { asm volatile("mbarrier.init.shared::cta.b64 [%0], %1;" ::"r"(a), "r"(cnt) : "memory"); }
__device__ __forceinline__ void mbar_expect_tx(uint32_t a, uint32_t bytes) { asm volatile("mbarrier.arrive.expect_tx.shared::cta.b64 _, [%0], %1;" ::"r"(a), "r"(bytes) : "memory"); }
__device__ __forceinline__ void mbar_wait(uint32_t a, uint32_t parity) {
    asm volatile("{.reg .pred p, q; .reg .u32 g; mov.u32 g, 0;\n"
                 "L: mbarrier.try_wait.parity.shared::cta.b64 p, [%0], %1;\n"
                 "add.u32 g, g, 1; setp.lt.and.u32 q, g, 0x400000, !p; @q bra L;}" ::"r"(a), "r"(parity) : "memory");
}
__device__ __forceinline__ bool mbar_test(uint32_t a, uint32_t parity) {
    uint32_t ok;
    asm volatile("{.reg .pred p; mbarrier.test_wait.parity.shared::cta.b64 p, [%1], %2; selp.u32 %0, 1, 0, p;}" : "=r"(ok) : "r"(a), "r"(parity) : "memory");
    return ok;
}
__device__ __forceinline__ bool elect() {
    uint32_t ok;
    asm volatile("{.reg .pred p; elect.sync _|p, 0xffffffff; selp.u32 %0, 1, 0, p;}" : "=r"(ok));
    return ok;
}
__device__ __forceinline__ void tma_box(const CUtensorMap* tm, uint32_t dst, uint32_t bar, int xq, int yq) {
    mbar_expect_tx(bar, XSTG / 4);
    asm volatile("cp.async.bulk.tensor.3d.shared::cluster.global.mbarrier::complete_tx::bytes [%0], [%1, {%3, %4, %5}], [%2];"
                 ::"r"(dst), "l"(tm), "r"(bar), "r"(0), "r"(xq), "r"(yq) : "memory");
}
__device__ __forceinline__ void tma_x(const CUtensorMap* tm, int slot, int q, int xq, int yq) { tma_box(tm, S_X + slot * XSTG + q * (XSTG / 4), S_BAR + 8 * slot, xq, yq); }
__device__ __forceinline__ void bulk_load(uint32_t dst, const void* src, uint32_t bytes, uint32_t bar) {
    mbar_expect_tx(bar, bytes);
    asm volatile("cp.async.bulk.shared::cluster.global.mbarrier::complete_tx::bytes [%0], [%1], %2, [%3];"
                 ::"r"(dst), "l"(src), "r"(bytes), "r"(bar) : "memory");
}
__device__ __forceinline__ void bulk_store(void* dst, uint32_t src, uint32_t bytes) {
    asm volatile("cp.async.bulk.global.shared::cta.bulk_group [%0], [%1], %2;" ::"l"(dst), "r"(src), "r"(bytes) : "memory");
}
__device__ __forceinline__ void bulk_commit() { asm volatile("cp.async.bulk.commit_group;" ::: "memory"); }
__device__ __forceinline__ void bulk_wait() { asm volatile("cp.async.bulk.wait_group 0;" ::: "memory"); }
__device__ __forceinline__ uint32_t lds32(uint32_t a) { uint32_t v; asm volatile("ld.shared.b32 %0, [%1];" : "=r"(v) : "r"(a)); return v; }
__device__ __forceinline__ void lds128(uint32_t* r, uint32_t a) { asm volatile("ld.shared.v4.b32 {%0,%1,%2,%3}, [%4];" : "=r"(r[0]), "=r"(r[1]), "=r"(r[2]), "=r"(r[3]) : "r"(a)); }
__device__ __forceinline__ void sts32(uint32_t a, uint32_t v) { asm volatile("st.shared.b32 [%0], %1;" ::"r"(a), "r"(v)); }
__device__ __forceinline__ void sts128(uint32_t a, uint32_t x, uint32_t y, uint32_t z, uint32_t w) { asm volatile("st.shared.v4.b32 [%0], {%1,%2,%3,%4};" ::"r"(a), "r"(x), "r"(y), "r"(z), "r"(w)); }
__device__ __forceinline__ void ldsm4(uint32_t& r0, uint32_t& r1, uint32_t& r2, uint32_t& r3, uint32_t a) {
    asm volatile("ldmatrix.sync.aligned.m8n8.x4.shared.b16 {%0,%1,%2,%3}, [%4];" : "=r"(r0), "=r"(r1), "=r"(r2), "=r"(r3) : "r"(a));
}
__device__ __forceinline__ void ldsm4(uint32_t* r, uint32_t a) { ldsm4(r[0], r[1], r[2], r[3], a); }
__device__ __forceinline__ void ldsm2(uint32_t& r0, uint32_t& r1, uint32_t a) {
    asm volatile("ldmatrix.sync.aligned.m8n8.x2.shared.b16 {%0,%1}, [%2];" : "=r"(r0), "=r"(r1) : "r"(a));
}
__device__ __forceinline__ void stsm4(uint32_t a, const uint32_t* r) {
    asm volatile("stmatrix.sync.aligned.m8n8.x4.shared.b16 [%4], {%0,%1,%2,%3};" ::"r"(r[0]), "r"(r[1]), "r"(r[2]), "r"(r[3]), "r"(a));
}
__device__ __forceinline__ uint32_t bfma(uint32_t a, uint32_t b, uint32_t c) { uint32_t d; asm("fma.rn.bf16x2 %0, %1, %2, %3;" : "=r"(d) : "r"(a), "r"(b), "r"(c)); return d; }
__device__ __forceinline__ uint32_t bmul(uint32_t a, uint32_t b) { uint32_t d; asm("mul.rn.bf16x2 %0, %1, %2;" : "=r"(d) : "r"(a), "r"(b)); return d; }
__device__ __forceinline__ uint32_t badd(uint32_t a, uint32_t b) { uint32_t d; asm("add.rn.bf16x2 %0, %1, %2;" : "=r"(d) : "r"(a), "r"(b)); return d; }
__device__ __forceinline__ uint32_t vfma(uint32_t a, uint32_t b, uint32_t c) { uint32_t d; asm volatile("fma.rn.bf16x2 %0, %1, %2, %3;" : "=r"(d) : "r"(a), "r"(b), "r"(c)); return d; }
__device__ __forceinline__ void vacc(uint32_t& d, uint32_t a, uint32_t b) { asm volatile("fma.rn.bf16x2 %0, %1, %2, %0;" : "+r"(d) : "r"(a), "r"(b)); }
__device__ __forceinline__ uint32_t vadd(uint32_t a, uint32_t b) { uint32_t d; asm volatile("add.rn.bf16x2 %0, %1, %2;" : "=r"(d) : "r"(a), "r"(b)); return d; }
__device__ __forceinline__ uint32_t vsub(uint32_t a, uint32_t b) { uint32_t d; asm volatile("sub.rn.bf16x2 %0, %1, %2;" : "=r"(d) : "r"(a), "r"(b)); return d; }
__device__ __forceinline__ uint32_t vmul(uint32_t a, uint32_t b) { uint32_t d; asm volatile("mul.rn.bf16x2 %0, %1, %2;" : "=r"(d) : "r"(a), "r"(b)); return d; }
__device__ __forceinline__ uint32_t habsmax(uint32_t a, uint32_t b) { uint32_t d; asm("max.xorsign.abs.bf16x2 %0, %1, %2;" : "=r"(d) : "r"(a), "r"(b)); return d; }
__device__ __forceinline__ float bf_lo(uint32_t v) { return __uint_as_float(v << 16); }
__device__ __forceinline__ float bf_hi(uint32_t v) { return __uint_as_float(v & 0xffff0000u); }
__device__ __forceinline__ uint32_t pack_h2(float lo, float hi) { uint32_t d; asm("cvt.rn.f16x2.f32 %0, %1, %2;" : "=r"(d) : "f"(hi), "f"(lo)); return d; }
__device__ __forceinline__ uint32_t pack_b2(float lo, float hi) { uint32_t d; asm("cvt.rn.bf16x2.f32 %0, %1, %2;" : "=r"(d) : "f"(hi), "f"(lo)); return d; }
__device__ __forceinline__ uint32_t b2h(uint32_t v) { return v + 7u * (v & 0x7fff7fffu); }
__device__ __forceinline__ float rsq(float v) { float r; asm("rsqrt.approx.ftz.f32 %0, %1;" : "=f"(r) : "f"(v)); return r; }

struct Conv {
    uint32_t w[50];
    uint32_t s[20];
    uint32_t accA[4][8], accB[4][4];
    uint32_t sink;
    bool on;
    uint32_t xa[2][12], xb[2][8];
};
template <int S, int P, int MODE>
__device__ __forceinline__ void tap_col(uint32_t x, const uint32_t* w, uint32_t (&d)[S], const uint32_t (&src)[S]) {
#pragma unroll
    for (int j = 4; j >= 0; j--) {
        const int q = P - j;
        if (q < 0 || q >= S) continue;
        if (j > 0 || MODE == 0) vacc(d[q], x, w[2 * j]);
        else if (MODE == 1) d[q] = vmul(x, w[0]);
        else d[q] = vfma(x, w[0], src[q]);
    }
}
template <int R, int K> __device__ __forceinline__ void conv_ld(Conv& c, uint32_t a1) {
    ldsm4(c.xa[R][2 * K + 2], c.xb[R][2 * K], c.xa[R][2 * K + 3], c.xb[R][2 * K + 1], a1 + K * 2 * PX);
}
#define CFN(n) { if ((CFENCE >> n) & 1) cfence(c.sink, c.on); }
#define ALLCOLS CA(0); CA(1); CA(2); CB(0); CA(3); CB(1); CA(4); CB(2); CA(5); CB(3); CA(6); CB(4); CA(7); CB(5); CA(8); CB(6); CA(9); CB(7); CA(10); CA(11);
template <int R, typename Fn>
__device__ __forceinline__ void conv_out(Conv& c, uint32_t sA, uint32_t sB, Fn before_store) {
#define CA(p) tap_col<8, p, 0>(c.xa[R][p], c.w + 41, c.accA[R], c.accA[R])
#define CB(p) tap_col<4, p, 0>(c.xb[R][p], c.w + 40, c.accB[R], c.accB[R])
    CA(0); CA(1); CA(2); CB(0); CA(3); CB(1); CA(4); CB(2); CA(5); CB(3); CA(6); CB(4); CA(7); CB(5);
    before_store();
    stsm4(sA, c.accA[R]);
    CA(8); CB(6); CA(9); CB(7); CA(10); CA(11);
    stsm4(sB, c.accB[R]);
    stsm4(sA + 4 * CPITCH, c.accA[R] + 4);
#undef CA
#undef CB
}
template <int S, int P, int R, bool OLD, bool NEW>
__device__ __forceinline__ void diff_col(const uint32_t (&x)[2][S + 4], const uint32_t* w, uint32_t (&acc)[4][S]) {
    if (!OLD && !NEW) return;
    const uint32_t d = vsub(x[0][P], x[1][P]);
    if (R == 1) {
        if (OLD) tap_col<S, P, 0>(d, w + 20, acc[0], acc[0]);
        if (NEW) tap_col<S, P, 2>(d, w, acc[2], acc[3]);
    } else {
        if (OLD) tap_col<S, P, 0>(d, w + 30, acc[1], acc[1]);
        if (NEW) tap_col<S, P, 0>(d, w + 10, acc[3], acc[3]);
    }
}
template <int R, bool OLD, bool NEW, typename Fn>
__device__ __forceinline__ void conv_rest(Conv& c, uint32_t a1, uint32_t a2, Fn mid) {
    if (R == 1) {
        if (OLD) {
#define CA(p) tap_col<8, p, 1>(c.xa[1][p], c.s + 11, c.accA[0], c.accA[0])
#define CB(p) tap_col<4, p, 1>(c.xb[1][p], c.s + 10, c.accB[0], c.accB[0])
            ALLCOLS
#undef CA
#undef CB
#pragma unroll
            for (int q = 0; q < 8; q++) { c.accA[1][q] = vadd(c.accA[3][q], c.accA[0][q]); c.accA[0][q] = vadd(c.accA[2][q], c.accA[0][q]); }
#pragma unroll
            for (int q = 0; q < 4; q++) { c.accB[1][q] = vadd(c.accB[3][q], c.accB[0][q]); c.accB[0][q] = vadd(c.accB[2][q], c.accB[0][q]); }
            CFN(7)
        }
        if (NEW) {
#define CA(p) tap_col<8, p, 1>(c.xa[1][p], c.s + 1, c.accA[3], c.accA[3])
#define CB(p) tap_col<4, p, 1>(c.xb[1][p], c.s, c.accB[3], c.accB[3])
            ALLCOLS
#undef CA
#undef CB
            CFN(8)
        }
    }
#define CA(p) diff_col<8, p, R, OLD, NEW>(c.xa, c.w + 1, c.accA)
#define CB(p) diff_col<4, p, R, OLD, NEW>(c.xb, c.w, c.accB)
    CA(0); CA(1); CFN(0)
    ldsm2(c.xa[1 - R][0], c.xa[1 - R][1], a2);
    CA(2); CB(0); CA(3); CB(1); CFN(1)
    conv_ld<1 - R, 0>(c, a1);
    CA(4); CB(2); CA(5); CB(3); CFN(2)
    conv_ld<1 - R, 1>(c, a1);
    CA(6); CB(4); CA(7); CB(5); CFN(3)
    conv_ld<1 - R, 2>(c, a1);
    CA(8); CB(6); CA(9); CB(7); CFN(4)
    conv_ld<1 - R, 3>(c, a1);
    CA(10); CA(11); CFN(5)
    ldsm2(c.xa[1 - R][10], c.xa[1 - R][11], a2 + 10 * PX);
    mid();
    CFN(9)
#undef CA
#undef CB
}
#undef ALLCOLS

template <int J, int K0, int K1> __device__ __forceinline__ void gemm1(uint32_t* H, const uint32_t* a1, uint64_t db) {
#pragma unroll
    for (int kk = K0; kk < K1; kk++) {
        const uint64_t d = mkd(db, D_W1 + ((2 * kk * 48 + J * 12) * 128 >> 4));
        if (kk == 0) wg_n96_h<0>(H + J * 24, a1, d);
        else wg_n96_h<1>(H + J * 24, a1 + 4 * kk, d);
    }
}
template <int K0, int K1> __device__ __forceinline__ void gemm2(uint32_t* acc, const uint32_t* H, uint64_t db) {
#pragma unroll
    for (int ks = K0; ks < K1; ks++) {
        const uint64_t d = mkd(db, D_W2 + (2 * ks * 12 * 128 >> 4));
        if (ks == 0) wg_n96_h<0>(acc, H, d);
        else wg_n96_h<1>(acc, H + 4 * ks, d);
    }
}
__device__ __forceinline__ uint32_t g_p(uint32_t s) { uint32_t d; asm volatile("fma.rn.f16x2 %0, %1, %1, %2;" : "=r"(d) : "r"(s), "r"(GK2)); return d; }
__device__ __forceinline__ uint32_t g_u(uint32_t s, uint32_t p) { uint32_t d; asm volatile("mul.rn.f16x2 %0, %1, %2;" : "=r"(d) : "r"(s), "r"(p)); return d; }
__device__ __forceinline__ uint32_t g_lo(uint32_t u) { uint32_t d; asm volatile("{.reg .b16 l, h, x; mov.b32 {l, h}, %1; tanh.approx.f16 x, l; cvt.u32.u16 %0, x;}" : "=r"(d) : "r"(u)); return d; }
__device__ __forceinline__ uint32_t g_hi(uint32_t u) { uint32_t d; asm volatile("{.reg .b16 l, h, x; mov.b32 {l, h}, %1; tanh.approx.f16 x, h; cvt.u32.u16 %0, x;}" : "=r"(d) : "r"(u)); return d; }
__device__ __forceinline__ uint32_t g_k(uint32_t a, uint32_t b) { uint32_t d; asm volatile("prmt.b32 %0, %1, %2, 0x5410;" : "=r"(d) : "r"(a), "r"(b)); return d; }
__device__ __forceinline__ uint32_t g_y(uint32_t s, uint32_t t) { uint32_t d; asm volatile("fma.rn.f16x2 %0, %1, %2, %1;" : "=r"(d) : "r"(s), "r"(t)); return d; }
template <int r> __device__ __forceinline__ void ln_part(const uint32_t* a, uint32_t* sq) {
    uint32_t s[6], q[2];
#pragma unroll
    for (int i = 0; i < 6; i++) s[i] = badd(a[4 * i + r], a[4 * i + 2 + r]);
    sq[r] = badd(badd(badd(s[0], s[1]), badd(s[2], s[3])), badd(s[4], s[5]));
#pragma unroll
    for (int i = 0; i < 12; i++) q[i & 1] = (i < 2) ? bmul(a[2 * i + r], a[2 * i + r]) : bfma(a[2 * i + r], a[2 * i + r], q[i & 1]);
    sq[2 + r] = badd(q[0], q[1]);
    pin<1>(sq + r); pin<1>(sq + 2 + r);
}
__device__ __forceinline__ void ln_mma(float* d, const uint32_t* sq, uint64_t db) {
    asm volatile("wgmma.mma_async.sync.aligned.m64n8k16.f32.bf16.bf16 {%0,%1,%2,%3}, {%4,%5,%6,%7}, %8, 0, 1, 1, 1;"
                 : "=f"(d[0]), "=f"(d[1]), "=f"(d[2]), "=f"(d[3]) : "r"(sq[0]), "r"(sq[1]), "r"(sq[2]), "r"(sq[3]), "l"(mkd(db, D_ST)));
}
__device__ __forceinline__ bool ln_fin(float* d, uint32_t* st) {
    pin<4>(d);
    bool risky = false;
#pragma unroll
    for (int r = 0; r < 2; r++) {
        const float q = rsq(fmaf(-d[2 * r], d[2 * r], d[2 * r + 1] + LN_EPS * (CH * CH)));
        const float z = d[2 * r] * q;
        risky |= !(fabsf(z) <= 1.f);
        st[r] = pack_b2(q * (LN_OUT * CH), z * -LN_OUT);
    }
    pin<2>(st);
    return __any_sync(0xffffffffu, risky);
}
__device__ __forceinline__ void ln_fix(uint32_t* a, const float* d, uint32_t* st) {
#pragma unroll
    for (int r = 0; r < 2; r++) {
        const uint32_t m2 = pack_b2(d[2 * r] * (-1.f / CH), d[2 * r] * (-1.f / CH));
        uint32_t q[2];
#pragma unroll
        for (int i = 0; i < 12; i++) {
            a[2 * i + r] = badd(a[2 * i + r], m2);
            q[i & 1] = (i < 2) ? bmul(a[2 * i + r], a[2 * i + r]) : bfma(a[2 * i + r], a[2 * i + r], q[i & 1]);
        }
        const uint32_t qq = badd(q[0], q[1]);
        float v = bf_lo(qq) + bf_hi(qq);
        v += __shfl_xor_sync(0xffffffffu, v, 1);
        v += __shfl_xor_sync(0xffffffffu, v, 2);
        st[r] = pack_b2(rsq(fmaf(v, 1.f / CH, LN_EPS)) * LN_OUT, 0.f);
    }
}
template <int I0, int I1> __device__ __forceinline__ void ln_out(uint32_t* a, const uint32_t* b, const uint32_t* st) {
#pragma unroll
    for (int i = I0; i < I1; i++) {
        uint32_t v;
        asm("{.reg .b16 l, h; .reg .b32 ll, hh; mov.b32 {l, h}, %2; mov.b32 ll, {l, l}; mov.b32 hh, {h, h}; fma.rn.bf16x2 %0, %1, ll, hh;}"
            : "=r"(v) : "r"(b[i]), "r"(st[i & 1]));
        a[i] = b2h(v);
        pin<1>(a + i);
    }
}
template <int J0, int J1> __device__ __forceinline__ void epi_mma(float* d, const uint32_t* acc, uint64_t db) {
    const uint64_t ds = mkd(db, D_ID);
#pragma unroll
    for (int j = J0; j < J1; j++)
        asm volatile("wgmma.mma_async.sync.aligned.m64n16k16.f32.f16.f16 {%0,%1,%2,%3,%4,%5,%6,%7}, {%8,%9,%10,%11}, %12, 0, 1, 1, 1;"
                     : "=f"(d[8 * j]), "=f"(d[8 * j + 1]), "=f"(d[8 * j + 2]), "=f"(d[8 * j + 3]), "=f"(d[8 * j + 4]), "=f"(d[8 * j + 5]), "=f"(d[8 * j + 6]), "=f"(d[8 * j + 7])
                     : "r"(acc[4 * j]), "r"(acc[4 * j + 1]), "r"(acc[4 * j + 2]), "r"(acc[4 * j + 3]), "l"(ds));
}
__device__ __forceinline__ void red128(uint8_t* gp, const uint32_t* o) {
    asm volatile("red.global.add.noftz.v4.bf16x2 [%0], {%1,%2,%3,%4};" ::"l"(gp), "r"(o[0]), "r"(o[1]), "r"(o[2]), "r"(o[3]));
}
template <int I> __device__ __forceinline__ void epi_red(const float* d, uint8_t* gp) {
#pragma unroll
    for (int r = 0; r < 2; r++) {
        uint32_t o[4];
#pragma unroll
        for (int jj = 0; jj < 4; jj++) o[jj] = pack_b2(d[16 * I + 4 * jj + 2 * r], d[16 * I + 4 * jj + 2 * r + 1]);
        red128(gp + r * 8 * PX + I * 64, o);
    }
}

template <int K> __device__ __forceinline__ void ln_step(float* d, float (&f)[2][2], uint32_t* st, bool& risky) {
    if (K == 0) pin<4>(d);
#pragma unroll
    for (int r = 0; r < 2; r++) {
        if (K == 0) f[r][0] = d[2 * r + 1] + LN_EPS * (CH * CH);
        if (K == 1) f[r][0] = fmaf(-d[2 * r], d[2 * r], f[r][0]);
        if (K == 2) f[r][0] = rsq(f[r][0]);
        if (K == 3) { f[r][1] = d[2 * r] * f[r][0]; f[r][0] *= LN_OUT * CH; }
        if (K == 4) st[r] = pack_b2(f[r][0], f[r][1] * -LN_OUT);
        if (K < 4) pin<K == 3 ? 2 : 1>(f[r]);
    }
    if (K == 4) { pin<2>(st); risky = __any_sync(0xffffffffu, !(fabsf(f[0][1]) <= 1.f) || !(fabsf(f[1][1]) <= 1.f)); }
}

struct Mlp {
    uint32_t H[96], p[96], u[96], tl[96], th[96], tk[96], a1[24], b[24], acc[24], st[2], sq[4], sink;
    float sd[4], dd[48];
    bool on;
};
template <bool FIRST, bool LAST>
__device__ __forceinline__ void mlp_tile(Mlp& m, const uint64_t db, const int wg, const uint32_t cb, uint8_t* op) {
    bool risky;
    uint32_t o[6][4], ls[2][6], lq[2][2], lm[24];
    float lf[2][2];
#define F wg_fence()
#define C wg_commit()
#define W(n) wg_wait<n>()
#define WX(n, nf, nl) wg_wait<FIRST ? nf : LAST ? nl : n>()
#define S cfence(m.sink, m.on);
#define FULL() { if (!LAST) bar_sync_wg<BAR_FULL>(wg); }
#define RELEASE() { if (!LAST) bar_arrive_wg<BAR_EMPTY>(wg); }
#define LDB(k0, k1) { if (!LAST) ldsm4(m.b + 4 * k0, cb + k0 * 32); }
#define GP(w) m.p[w] = g_p(m.H[w])
#define GU(w) m.u[w] = g_u(m.H[w], m.p[w])
#define ML(w) m.tl[w] = g_lo(m.u[w])
#define MH(w) m.th[w] = g_hi(m.u[w])
#define GK(w) m.tk[w] = g_k(m.tl[w], m.th[w])
#define GY(w) m.H[w] = g_y(m.H[w], m.tk[w])
#define GPX(w) if (!LAST) GP(w)
#define GUX(w) if (!LAST) GU(w)
#define MLX(w) if (!LAST) ML(w)
#define MHX(w) if (!LAST) MH(w)
#define GKX(w) if (!LAST) GK(w)
#define G1(j, k0, k1) gemm1<j, k0, k1>(m.H, m.a1, db)
#define G2(k0, k1) gemm2<k0, k1>(m.acc, m.H, db)
#define RDY(j) { if (!LAST || j != 0) pin<24>(m.H + (j) * 24); }
#define IDM(j0, j1) epi_mma<j0, j1>(m.dd, m.acc, db)
#define IDR(j0, j1) { if (!FIRST) pin<8 * (j1 - j0)>(m.dd + 8 * j0); }
#define EP(I, r, jj) if (!FIRST) asm volatile("cvt.rn.bf16x2.f32 %0, %1, %2;" : "=r"(o[2 * I + r][jj]) : "f"(m.dd[16 * I + 4 * jj + 2 * r + 1]), "f"(m.dd[16 * I + 4 * jj + 2 * r]))
#define ES(I, r) if (!FIRST) red128(op + r * 8 * PX + I * 64, o[2 * I + r])
#define ER(I) { EP(I, 0, 0); EP(I, 0, 1); EP(I, 0, 2); EP(I, 0, 3); ES(I, 0); EP(I, 1, 0); EP(I, 1, 1); EP(I, 1, 2); EP(I, 1, 3); ES(I, 1); }
#define LO(i) { LO1(i); LO2(i); LO3(i); }
#define LS(i, r) if (!LAST) ls[r][i] = vadd(m.b[4 * i + r], m.b[4 * i + 2 + r])
#define LQ(i, r) if (!LAST) { if (i < 2) lq[r][i & 1] = vmul(m.b[2 * i + r], m.b[2 * i + r]); else vacc(lq[r][i & 1], m.b[2 * i + r], m.b[2 * i + r]); }
#define LT(k, r) if (!LAST) { if (k < 3) ls[r][2 * k % 6] = vadd(ls[r][2 * k % 6], ls[r][(2 * k + 1) % 6]); else if (k == 3) ls[r][0] = vadd(ls[r][0], ls[r][2]); \
                              else if (k == 4) m.sq[r] = vadd(ls[r][0], ls[r][4]); else m.sq[2 + r] = vadd(lq[r][0], lq[r][1]); }
#define LM() ln_mma(m.sd, m.sq, db)
#define LF(k) if (!LAST) ln_step<k>(m.sd, lf, m.st, risky)
#define LX2() { if (!LAST && __builtin_expect(risky, 0)) ln_fix(m.b, m.sd, m.st); }
#define LO1(i) if (!LAST) asm volatile("{.reg .b16 l, h; .reg .b32 ll, hh; mov.b32 {l, h}, %2; mov.b32 ll, {l, l}; mov.b32 hh, {h, h}; fma.rn.bf16x2 %0, %1, ll, hh;}" : "=r"(m.b[i]) : "r"(m.b[i]), "r"(m.st[i & 1]))
#define LO2(i) if (!LAST) asm volatile("and.b32 %0, %1, 0x7fff7fff;" : "=r"(lm[i]) : "r"(m.b[i]))
#define LO3(i) if (!LAST) asm volatile("mad.lo.u32 %0, %1, 7, %2;" : "=r"(m.a1[i]) : "r"(lm[i]), "r"(m.b[i]))
    F; if (!FIRST) { IDM(0,2); C; } G1(1,0,1); G1(1,1,2); G1(1,2,3); G1(1,3,4); G1(1,4,5); G1(1,5,6); C; ML(6); GU(7); GP(8); MH(6); GY(4); GY(0);
        GK(5); ML(7); GU(8); GP(9); MH(7); GY(5); GY(1); GK(6); ML(8); GU(9); GP(10); MH(8); GY(6); GY(2); GK(7); ML(9); GU(10); GP(11); MH(9); GY(7);
        GY(3); GK(8); S
    WX(1,1,1); IDR(0,2); ML(10); GU(11); GP(12); MH(10); GY(8); GK(9); ML(11); GU(12); GP(13); MH(11); GY(9); GK(10); ML(12); GU(13); GP(14); MH(12);
        GY(10); GK(11); ML(13); GU(14); GP(15); MH(13); GY(11); GK(12); ER(0); S
    if (!FIRST) { F; IDM(2,6); C; } ML(14); GU(15); GP(16); MH(14); GY(12); GK(13); ML(15); GU(16); GP(17); MH(15); GY(13); GK(14); ML(16); GU(17);
        GP(18); MH(16); GY(14); GK(15); ML(17); GU(18); GP(19); MH(17); GY(15); GK(16); S
    WX(0,0,0); IDR(2,6); F; G2(0,1); G2(1,2); G2(2,3); G2(3,4); C; ML(18); GU(19); GP(20); MH(18); GY(16); GK(17); ML(19); GU(20); GP(21); MH(19);
        GY(17); GK(18); S ML(20); GU(21); GP(22); MH(20); GY(18); GK(19); ML(21); GU(22); GP(23); MH(21); GY(19); GK(20); ER(1); S
    RDY(1); ML(22); GU(23); GP(24); MH(22); GY(20); GK(21); ML(23); GU(24); GP(25); MH(23); GY(21); GK(22); ML(24); GU(25); GP(26); MH(24); GY(22);
        GK(23); ML(25); GU(26); GP(27); MH(25); GY(23); GK(24); ER(2); S
    F; G1(2,0,1); G2(4,5); G1(2,1,2); G2(5,6); G1(2,2,3); G1(2,3,4); C; ML(26); GU(27); GP(28); MH(26); GY(24); GK(25); ML(27); GU(28); GP(29);
        MH(27); GY(25); GK(26); ML(28); GU(29); GP(30); MH(28); GY(26); GK(27); ML(29); GU(30); GP(31); MH(29); GY(27); GK(28); S
    F; G1(2,4,5); G1(2,5,6); C; ML(30); GU(31); GP(32); MH(30); GY(28); GK(29); ML(31); GU(32); GP(33); MH(31); GY(29); GK(30); S ML(32); GU(33);
        GP(34); MH(32); GY(30); GK(31); ML(33); GU(34); GP(35); MH(33); GY(31); GK(32); S
    WX(2,2,2); F; G2(6,7); G2(7,8); C; ML(34); GU(35); GP(36); MH(34); GY(32); GK(33); ML(35); GU(36); GP(37); MH(35); GY(33); GK(34); ML(36); GU(37);
        GP(38); MH(36); GY(34); GK(35); ML(37); GU(38); GP(39); MH(37); GY(35); GK(36); S
    ML(38); GU(39); GP(40); MH(38); GY(36); GK(37); ML(39); GU(40); GP(41); MH(39); GY(37); GK(38); ML(40); GU(41); GP(42); MH(40); GY(38); GK(39);
        ML(41); GU(42); GP(43); MH(41); GY(39); GK(40); S
    WX(2,2,2); F; G2(8,9); G2(9,10); C; ML(42); GU(43); GP(44); MH(42); GY(40); GK(41); ML(43); GU(44); GP(45); MH(43); GY(41); GK(42); ML(44);
        GU(45); GP(46); MH(44); GY(42); GK(43); ML(45); GU(46); GP(47); MH(45); GY(43); GK(44); S
    FULL() LDB(0,1) LDB(1,2) LDB(2,3) WX(2,2,2); RDY(2); ML(46); GU(47); GP(48); MH(46); GY(44); GK(45); ML(47); GU(48); GP(49); MH(47); GY(45);
        GK(46); ML(48); GU(49); GP(50); MH(48); GY(46); GK(47); ML(49); GU(50); GP(51); MH(49); GY(47); GK(48); S
    LDB(3,4) LDB(4,5) LDB(5,6) WX(1,1,1); F; G1(3,0,1); G2(10,11); G1(3,1,2); G2(11,12); G1(3,2,3); G1(3,3,4); C; ML(50); GU(51); GP(52); MH(50);
        GY(48); GK(49); ML(51); GU(52); GP(53); MH(51); GY(49); GK(50); ML(52); GU(53); GP(54); MH(52); GY(50); GK(51); ML(53); GU(54); GP(55);
        MH(53); GY(51); GK(52); S
    ML(54); GU(55); GP(56); MH(54); GY(52); GK(53); ML(55); GU(56); GP(57); MH(55); GY(53); GK(54); ML(56); GU(57); GP(58); MH(56); GY(54); GK(55);
        ML(57); GU(58); GP(59); MH(57); GY(55); GK(56); LS(0,0); LS(0,1); LQ(0,0); LQ(0,1); LQ(1,0); LQ(1,1); LS(1,0); LS(1,1); LQ(2,0); LQ(2,1);
        LQ(3,0); LQ(3,1); LS(2,0); LS(2,1); LQ(4,0); LQ(4,1); LQ(5,0); LQ(5,1); LS(3,0); LS(3,1); LQ(6,0); LQ(6,1); LQ(7,0); LQ(7,1); LS(4,0);
        LS(4,1); LQ(8,0); LQ(8,1); LQ(9,0); LQ(9,1); LS(5,0); LS(5,1); LQ(10,0); LQ(10,1); LQ(11,0); LQ(11,1); LT(0,0); LT(0,1); LT(1,0); LT(1,1);
        LT(2,0); LT(2,1); LT(5,0); LT(5,1); LT(3,0); LT(3,1); LT(4,0); LT(4,1); S
    WX(1,1,1); F; if (!LAST) { LM(); C; } G1(3,4,5); G2(12,13); G1(3,5,6); G2(13,14); C; ML(58); GU(59); GP(60); MH(58); GY(56); GK(57); ML(59);
        GU(60); GP(61); MH(59); GY(57); GK(58); ML(60); GU(61); GP(62); MH(60); GY(58); GK(59); ML(61); GU(62); GP(63); MH(61); GY(59); GK(60); S
    WX(1,1,1); ML(62); GU(63); GP(64); MH(62); GY(60); GK(61); ML(63); GU(64); GP(65); MH(63); GY(61); GK(62); ML(64); GU(65); GP(66); MH(64); GY(62);
        GK(63); ML(65); GU(66); GP(67); MH(65); GY(63); GK(64); LF(0); LF(1); LF(2); LF(3); LF(4); S LX2()
    F; G2(14,15); G2(15,16); C; ML(66); GU(67); GP(68); MH(66); GY(64); GK(65); ML(67); GU(68); GP(69); MH(67); GY(65); GK(66); ML(68); GU(69);
        GP(70); MH(68); GY(66); GK(67); ML(69); GU(70); GP(71); MH(69); GY(67); GK(68); S
    WX(1,1,1); RDY(3); ML(70); GU(71); GP(72); MH(70); GY(68); GK(69); ML(71); GU(72); GP(73); MH(71); GY(69); GK(70); ML(72); GU(73); GP(74); MH(72);
        GY(70); GK(71); ML(73); GU(74); GP(75); MH(73); GY(71); GK(72); LO(0); LO(1); LO(2); LO(3); LO(4); LO(5); LO(6); LO(7); LO(8); LO(9); LO(10);
        LO(11); LO(12); LO(13); LO(14); LO(15); LO(16); LO(17); LO(18); LO(19); LO(20); LO(21); LO(22); LO(23); S
    F; if (!LAST) G1(0,0,1); G2(16,17); if (!LAST) G1(0,1,2); G2(17,18); if (!LAST) G1(0,2,3); C; ML(74); GU(75); GP(76); MH(74); GY(72); GK(73);
        ML(75); GU(76); GP(77); MH(75); GY(73); GK(74); ML(76); GU(77); GP(78); MH(76); GY(74); GK(75); ML(77); GU(78); GP(79); MH(77); GY(75);
        GK(76); S
    ML(78); GU(79); GP(80); MH(78); GY(76); GK(77); ML(79); GU(80); GP(81); MH(79); GY(77); GK(78); ML(80); GU(81); GP(82); MH(80); GY(78); GK(79);
        ML(81); GU(82); GP(83); MH(81); GY(79); GK(80); S
    WX(1,1,1); F; if (!LAST) G1(0,3,4); G2(18,19); if (!LAST) G1(0,4,5); G2(19,20); if (!LAST) G1(0,5,6); C; ML(82); GU(83); GP(84); MH(82); GY(80);
        GK(81); ML(83); GU(84); GP(85); MH(83); GY(81); GK(82); ML(84); GU(85); GP(86); MH(84); GY(82); GK(83); ML(85); GU(86); GP(87); MH(85);
        GY(83); GK(84); S
    ML(86); GU(87); GP(88); MH(86); GY(84); GK(85); ML(87); GU(88); GP(89); MH(87); GY(85); GK(86); ML(88); GU(89); GP(90); MH(88); GY(86); GK(87);
        ML(89); GU(90); GP(91); MH(89); GY(87); GK(88); S
    WX(1,1,1); F; G2(20,21); G2(21,22); C; ML(90); GU(91); GP(92); MH(90); GY(88); GK(89); ML(91); GU(92); GP(93); MH(91); GY(89); GK(90); ML(92);
        GU(93); GP(94); MH(92); GY(90); GK(91); ML(93); GU(94); GP(95); MH(93); GY(91); GK(92); S
    RELEASE() WX(1,1,1); RDY(0); ML(94); GU(95); GPX(0); MH(94); GY(92); GK(93); ML(95); GUX(0); GPX(1); MH(95); GY(93); GK(94); MLX(0); GUX(1);
        GPX(2); MHX(0); GY(94); GK(95); MLX(1); GUX(2); GPX(3); MHX(1); GY(95); GKX(0); S
    F; G2(22,23); G2(23,24); C; MLX(2); GUX(3); GPX(4); MHX(2); GKX(1); MLX(3); GUX(4); GPX(5); MHX(3); GKX(2); MLX(4); GUX(5); GPX(6); MHX(4);
        GKX(3); MLX(5); GUX(6); GPX(7); MHX(5); GKX(4); S
    W(0);
    pin<24>(m.acc);
#undef F
#undef C
#undef W
#undef WX
#undef S
#undef FULL
#undef RELEASE
#undef LDB
#undef GP
#undef GU
#undef ML
#undef MH
#undef GK
#undef GY
#undef GPX
#undef GUX
#undef MLX
#undef MHX
#undef GKX
#undef G1
#undef G2
#undef RDY
#undef IDM
#undef IDR
#undef EP
#undef ES
#undef LS
#undef ER
#undef LO
#undef LQ
#undef LT
#undef LM
#undef LF
#undef LX2
#undef LO1
#undef LO2
#undef LO3
}

__global__ void __launch_bounds__(384, 1)
replk_kernel(const __grid_constant__ CUtensorMap tmx, const uint8_t* __restrict__ dwl, const uint8_t* __restrict__ dws,
             const uint8_t* __restrict__ w1, const uint8_t* __restrict__ w2, uint8_t* __restrict__ out, const uint64_t db,
             unsigned long long* __restrict__ dbg) {
    extern __shared__ __align__(1024) uint8_t smem[];
    const int tid = (threadIdx.x + ROT * 128) % 384, lane = tid & 31;
    const int warp = __shfl_sync(0xffffffffu, tid >> 5, 0);
    const int w0 = (blockIdx.x % (IMG_W / SW)) * SW, y0 = (blockIdx.x / (IMG_W / SW)) * RB;
    const int up = 1 & ~(blockIdx.x / (IMG_W / SW));
    const int dy = 1 - 2 * up, yb = y0 - 2 + (RB + 3) * up;
    if (tid == 0) sts32(S_RED + 40, (uint32_t)clock64());

    if (warp >= 8) {
        const int cw = warp - 8;
        const int tj = min((tid - 256) / 24, 4), tc = (tid - 256) % 24;
        uint2 ts[5], tl[3];
#pragma unroll
        for (int i = 0; i < 5; i++) ts[i] = __ldg(reinterpret_cast<const uint2*>(dws) + ((2 + dy * (i - 2)) * 5 + tj) * 24 + tc);
#pragma unroll
        for (int i = 0; i < 3; i++) tl[i] = __ldg(reinterpret_cast<const uint2*>(dwl) + ((1 + dy * (i - 1)) * 3 + (tj + 2) % 3) * 24 + tc);
        if (cw == 0 && elect()) {
            if ((uint32_t)__cvta_generic_to_shared(smem) != SB) __trap();
#pragma unroll
            for (int s = 0; s < NS; s++) mbar_init(S_BAR + 8 * s, 4);
            asm volatile("fence.mbarrier_init.release.cluster;" ::: "memory");
#pragma unroll
            for (int q = 0; q < 4; q++) tma_x(&tmx, 0, q, w0 - 2 + (q & 1) * 18, yb + dy * (q >> 1));
        }
        bar_sync(BAR_CV, 128);
        const int xq = w0 - 2 + (cw & 1) * 18, yq = yb + dy * (cw >> 1);
        if (elect()) tma_x(&tmx, 1, cw, xq, yq + 2 * dy);
        Conv c;
        {
            const uint32_t lm = (tj & 3) ? ~0u : 0u;
            uint32_t v[7][2];
#pragma unroll
            for (int i = 0; i < 5; i++) {
                v[i][0] = ts[i].x; v[i][1] = ts[i].y;
                if (i >= 1 && i <= 3) { v[i][0] = badd(v[i][0], tl[i - 1].x & lm); v[i][1] = badd(v[i][1], tl[i - 1].y & lm); }
                v[i][0] = bmul(v[i][0], WSC2); v[i][1] = bmul(v[i][1], WSC2);
            }
#pragma unroll
            for (int u = 0; u < 2; u++) { v[5][u] = badd(v[0][u], v[1][u]); v[6][u] = badd(v[2][u], v[3][u]); }
#pragma unroll
            for (int i = 0; i < 7; i++)
                asm volatile("st.shared.v2.b32 [%0], {%1, %2};" ::"r"(S_C + ((i * 5 + tj) * 24 + tc) * 8), "r"(v[i][0]), "r"(v[i][1]) : "memory");
            bar_sync(BAR_CV, 128);
            if (elect()) tma_x(&tmx, 2, cw, xq, yq + 4 * dy);
            const int qd = lane & 7, u = (lane >> 3) & 1;
            const uint32_t ws = S_C + ((cw < 2 + u) ? qd : 8 + (qd & 3)) * 16;
#pragma unroll
            for (int k = 0; k < 12; k++) ldsm4(c.w + 4 * k, ws + ((lane >> 4) + 2 * k) * PX);
            ldsm2(c.w[48], c.w[49], ws + 24 * PX);
#pragma unroll
            for (int k = 0; k < 5; k++) ldsm4(c.s + 4 * k, ws + ((lane >> 4) + 25 + 2 * k) * PX);
        }
        const int mi = lane >> 3, qd = lane & 7;
        const int chA = (cw < 3) ? qd : 8 + (qd & 3), pxA = (cw < 3) ? 8 * cw : 16 * (qd >> 2);
        const int chB = (cw < 2) ? qd : 8 + (qd & 3), pxB = (cw < 2) ? 24 + 4 * cw : 16 * (qd >> 2) + 8 + 4 * (cw - 2);
        const uint32_t a1 = S_X + ((mi & 1) ? (pxB + (mi >> 1)) * PX + chB * 16 : (pxA + 2 + (mi >> 1)) * PX + chA * 16);
        const uint32_t a2 = S_X + (pxA + (mi & 1)) * PX + chA * 16;
        uint32_t qA = S_C + (pxA >> 4) * CGRP + ((pxA & 15) + mi) * CPITCH + chA * 16;
        uint32_t qB = S_C + (pxB >> 4) * CGRP + ((pxB & 15) + mi) * CPITCH + chB * 16;
        auto nop = [] {};
        c.sink = lane; c.on = lane == (int)(db >> 8);
        mbar_wait(S_BAR, 0);
        ldsm2(c.xa[0][0], c.xa[0][1], a2);
        conv_ld<0, 0>(c, a1); conv_ld<0, 1>(c, a1); conv_ld<0, 2>(c, a1); conv_ld<0, 3>(c, a1);
        ldsm2(c.xa[0][10], c.xa[0][11], a2 + 10 * PX);
        conv_rest<0, false, false>(c, a1 + XROW, a2 + XROW, nop);
        if (elect()) tma_x(&tmx, 3, cw, xq, yq + 6 * dy);
        mbar_wait(S_BAR + 8, 0);
        const uint32_t xs0 = S_X + (cw >> 1) * XROW + (2 + 16 * (cw & 1)) * PX;
        uint8_t* op = out + (size_t)((yq + 2 * dy) * IMG_W + w0 + 16 * (cw & 1)) * PX;
        const int64_t ostep = 2 * dy * IMG_W * PX;
        if (elect()) bulk_store(op, xs0 + XSTG, 16 * PX);
        bulk_commit();
        conv_rest<1, false, true>(c, a1 + XSTG, a2 + XSTG, nop);
        conv_rest<0, false, true>(c, a1 + XSTG + XROW, a2 + XSTG + XROW, nop);
        bar_sync(BAR_CV, 128);
        if (elect()) tma_x(&tmx, 0, cw, xq, yq + 8 * dy);
        mbar_wait(S_BAR + 16, 0);
        uint32_t u;
        asm volatile("mov.u32 %0, 24;" : "=r"(u));
        const uint32_t xd0 = S_X + cw * (XSTG / 4) - S_BAR * (XSTG / 8);
        uint32_t xo = 2 * XSTG, bid = BAR_EMPTY;
        int dq = CBUF, yn = yq + 10 * dy;
#pragma unroll 1
        for (;;) {
            const uint32_t nb = S_BAR | (u & 24), np = u >> 5;
            bool ok;
            conv_rest<1, true, true>(c, a1 + xo, a2 + xo, nop);
            conv_out<0>(c, qA, qB, [&] {
                bulk_wait();
                op += ostep;
                bar_sync(bid, 256);
                if (elect()) {
                    tma_box(&tmx, (nb ^ 16) * (XSTG / 8) + xd0, nb ^ 16, xq, u < 8 * NT ? yn : -8);
                    bulk_store(op, xs0 + xo, 16 * PX);
                }
                bulk_commit();
            });
            CFN(6)
            conv_rest<0, true, true>(c, a1 + xo + XROW, a2 + xo + XROW, [&] { ok = mbar_test(nb, np); });
            conv_out<1>(c, qA + 2 * CGRP, qB + 2 * CGRP, nop);
            bar_arrive(bid - (BAR_EMPTY - BAR_FULL), 256);
            xo = (u & 24) * (XSTG / 8); qA += dq; qB += dq; dq = -dq;
            asm volatile("" : "+r"(xo));
            yn += 2 * dy; bid ^= 1; u += 8;
            if (ok && u < 8 * (NT + 2)) continue;
            mbar_wait(nb, np);
            if (u == 8 * (NT + 2)) break;
        }
        conv_rest<1, true, false>(c, a1 + xo, a2 + xo, nop);
        conv_out<0>(c, qA, qB, [&] { bulk_wait(); bar_sync(BAR_EMPTY + 1, 256); });
        conv_rest<0, true, false>(c, a1 + xo + XROW, a2 + xo + XROW, nop);
        conv_out<1>(c, qA + 2 * CGRP, qB + 2 * CGRP, nop);
        bar_arrive(BAR_FULL + 1, 256);
        bar_arrive(BAR_EMPTY, 256);
        bar_arrive(BAR_EMPTY + 1, 256);
        mbar_wait(S_BAR + 8 * 2, 0);
        mbar_wait(S_BAR + 8 * 3, 0);
        if (dbg) sts32(S_RED + 36, c.sink);
    } else {
        const int wg = warp >> 2, wq = warp & 3;
        if (warp == 0 && elect()) {
#pragma unroll
            for (int s = 0; s < 5; s++) mbar_init(S_WBAR + 8 * s, 1);
            asm volatile("fence.mbarrier_init.release.cluster;" ::: "memory");
#pragma unroll
            for (int i = 0; i < 2; i++) bulk_load(S_W2 + i * (WBYTES / 2), w2 + i * (WBYTES / 2), WBYTES / 2, S_WBAR + 24 + 8 * i);
        }
        bar_arrive(BAR_EMPTY + wg, 256);
        if (tid < 64) sts32(S_ST + tid * 4, tid < 32 ? 0x00003f80u : 0x42c00000u);
        bar_sync(BAR_W, 256);
        {
            uint32_t r[18][4], mx = 0;
#pragma unroll
            for (int h = 0; h < 2; h++) {
                mbar_wait(S_WBAR + 24 + 8 * h, 0);
                if (h == 0 && warp == 0 && elect()) {
#pragma unroll
                    for (int i = 0; i < 3; i++) bulk_load(S_W1 + i * (WBYTES / 3), w1 + i * (WBYTES / 3), WBYTES / 3, S_WBAR + 8 * i);
                }
#pragma unroll
                for (int j = 0; j < 9; j++) {
                    uint32_t* q = r[h * 9 + j];
                    lds128(q, S_W2 + h * (WBYTES / 2) + (warp * 3 + j / 3) * 1536 + (lane >> 2) * PX + (j % 3) * 64 + (lane & 3) * 16);
                    mx = habsmax(habsmax(mx, q[0]), habsmax(habsmax(q[1], q[2]), q[3]));
                }
            }
            mx &= 0x7fff7fffu;
            mx = __reduce_max_sync(0xffffffffu, max(mx >> 16, mx & 0xffffu));
            if (lane == 0) sts32(S_RED + warp * 4, mx);
            bar_sync(BAR_W, 256);
            mx = __reduce_max_sync(0xffffffffu, lds32(S_RED + (lane & 7) * 4));
            const int e = max(min(123 - (int)(mx >> 7), 14), -14);
            const uint32_t wsc2 = (uint32_t)(15 + e) * 0x00800080u;
            if (tid < 128) {
                const int cm = tid >> 5, k = (tid >> 2) & 7, q = tid & 3;
                const uint32_t cv = INV2A_H - (e << 10);
                sts32(S_ID + tid * 4, (cm == 0 || cm == 3) && (k >> 1) == q ? cv << (16 * (k & 1)) : 0u);
            }
#pragma unroll
            for (int j = 0; j < 18; j++) {
#pragma unroll
                for (int k = 0; k < 4; k++) r[j][k] = b2h(bmul(r[j][k], wsc2));
                stsm4(S_W2 + (j / 9) * (WBYTES / 2) + (warp * 3 + j % 9 / 3) * 1536 + (j % 3) * 512 + lane * 16, r[j]);
            }
        }
        {
            const int kr = lane & 7, nb = (kr + wg * 4 + (lane >> 3)) & 7;
#pragma unroll 1
            for (int i = 0; i < 3; i++) {
                const uint32_t base = S_W1 + (i * 4 + wq) * 6144;
                uint32_t r[6][4];
                mbar_wait(S_WBAR + 8 * i, 0);
#pragma unroll
                for (int j = 0; j < 6; j++) lds128(r[j], base + kr * 768 + (j * 8 + nb) * 16);
                bar_sync(BAR_PAIR + wq, 64);
#pragma unroll
                for (int j = 0; j < 6; j++)
                    sts128(base + kr * 16 + (j * 8 + nb) * 128, pack_h2(bf_lo(r[j][0]), bf_hi(r[j][0])), pack_h2(bf_lo(r[j][1]), bf_hi(r[j][1])),
                           pack_h2(bf_lo(r[j][2]), bf_hi(r[j][2])), pack_h2(bf_lo(r[j][3]), bf_hi(r[j][3])));
            }
        }
        asm volatile("fence.proxy.async.shared::cta;" ::: "memory");
        const uint32_t cb = S_C + wg * CBUF + wq * CGRP + (lane & 15) * CPITCH + (lane >> 4) * 16;
        const uint32_t goff = ((yb + dy * (2 + 2 * wg + (wq >> 1))) * IMG_W + w0 + (wq & 1) * 16 + (lane >> 2)) * PX + (lane & 3) * 16;
        const int64_t gstep = dy * TSTEP;
        uint8_t* op = out;
        Mlp m;
        m.sink = lane; m.on = lane == (int)(db >> 8);
        bar_sync(BAR_W, 256);
        bar_sync(BAR_FULL + wg, 256);
#pragma unroll
        for (int kk = 0; kk < 6; kk++) ldsm4(m.b + 4 * kk, cb + kk * 32);
        bar_arrive(BAR_EMPTY + wg, 256);
        ln_part<0>(m.b, m.sq); ln_part<1>(m.b, m.sq);
        wg_fence(); ln_mma(m.sd, m.sq, DB); wg_commit(); wg_wait<0>();
        if (ln_fin(m.sd, m.st)) ln_fix(m.b, m.sd, m.st);
        ln_out<0, 24>(m.a1, m.b, m.st);
        wg_fence(); gemm1<0, 0, 6>(m.H, m.a1, DB); wg_commit(); wg_wait<0>();
        pin<24>(m.H);
#pragma unroll
        for (int w = 0; w < YLAG + HOLD + 2; w++) m.p[w] = g_p(m.H[w]);
#pragma unroll
        for (int w = 0; w < YLAG + HOLD + 1; w++) m.u[w] = g_u(m.H[w], m.p[w]);
#pragma unroll
        for (int w = 0; w < YLAG + HOLD; w++) { m.tl[w] = g_lo(m.u[w]); m.th[w] = g_hi(m.u[w]); }
#pragma unroll
        for (int w = 0; w <= HOLD; w++) m.tk[w] = g_k(m.tl[w], m.th[w]);
        mlp_tile<true, false>(m, DB, wg, cb, nullptr);
        int i;
        asm volatile("mov.u32 %0, 1;" : "=r"(i));
#pragma unroll 1
        do {
            mlp_tile<false, false>(m, db, wg, cb, op + goff);
            op += gstep;
            asm volatile("" : "+l"(op));
        } while (++i < NT / 2 - 1);
        op += goff;
        mlp_tile<false, true>(m, db, wg, cb, op);
        op += gstep;
        wg_fence(); epi_mma<0, 6>(m.dd, m.acc, db); wg_commit(); wg_wait<0>();
        pin<48>(m.dd);
        epi_red<0>(m.dd, op); epi_red<1>(m.dd, op); epi_red<2>(m.dd, op);
        if (dbg) {
            sts32(S_RED + 36, m.sink);
            uint32_t tx;
            asm volatile("mov.u32 %0, %%tid.x;" : "=r"(tx));
            if ((tx & 127) == 0) atomicAdd(dbg + (tx >> 7), (unsigned long long)((uint32_t)clock64() - lds32(S_RED + 40)));
        }
    }
}
#undef CFN

typedef CUresult (*EncodeFn)(CUtensorMap*, CUtensorMapDataType, cuuint32_t, void*, const cuuint64_t*, const cuuint64_t*,
                             const cuuint32_t*, const cuuint32_t*, CUtensorMapInterleave, CUtensorMapSwizzle,
                             CUtensorMapL2promotion, CUtensorMapFloatOOBfill);

}

#define DBG_PTR nullptr
extern "C" void kernel_launch(void* const* d_in, const int* in_sizes, int n_in, void* d_out, int out_size) {
    static EncodeFn enc = nullptr;
    if (!enc) {
        void* fn = nullptr;
        cudaDriverEntryPointQueryResult qr;
        cudaGetDriverEntryPoint("cuTensorMapEncodeTiled", &fn, cudaEnableDefault, &qr);
        enc = (EncodeFn)fn;
        cudaFuncSetAttribute(replk_kernel, cudaFuncAttributeMaxDynamicSharedMemorySize, SMEM_BYTES);
    }
    CUtensorMap tm;
    const cuuint64_t gdim[3] = {CH, IMG_W, IMG_H};
    const cuuint64_t gstr[2] = {PX, (cuuint64_t)IMG_W * PX};
    const cuuint32_t box[3] = {CH, (SW + 4) / 2, 1};
    const cuuint32_t estr[3] = {1, 1, 1};
    enc(&tm, CU_TENSOR_MAP_DATA_TYPE_BFLOAT16, 3, d_in[0], gdim, gstr, box, estr, CU_TENSOR_MAP_INTERLEAVE_NONE,
        CU_TENSOR_MAP_SWIZZLE_NONE, CU_TENSOR_MAP_L2_PROMOTION_L2_128B, CU_TENSOR_MAP_FLOAT_OOB_FILL_NONE);
    replk_kernel<<<(IMG_W / SW) * (IMG_H / RB), 384, SMEM_BYTES>>>(
        tm, (const uint8_t*)d_in[1], (const uint8_t*)d_in[2], (const uint8_t*)d_in[3], (const uint8_t*)d_in[4], (uint8_t*)d_out, DB, DBG_PTR);
}
```
